```python
import torch

def _softmax(x, axis=-1):
    return torch.softmax(x, dim=axis)
def _gelu(x):
    return torch.nn.functional.gelu(x, approximate="tanh")
def _silu(x):
    return torch.nn.functional.silu(x)
def _sigmoid(x):
    return torch.sigmoid(x)
def _layernorm(x, axis=-1, eps=1e-5):
    m = x.mean(dim=axis, keepdim=True)
    v = x.var(dim=axis, keepdim=True, unbiased=False)
    return (x - m) / torch.sqrt(v + eps)
def _scatter_add(tgt, idx, src, axis=0):
    return tgt.clone().index_add_(axis, idx, src)
def _segment_sum(src, seg, n):
    out = torch.zeros((n,) + src.shape[1:], dtype=src.dtype)
    return out.index_add_(0, seg, src)
def _pad(x, pw):
    flat = tuple(v for pair in reversed(pw) for v in pair)
    return torch.nn.functional.pad(x, flat)

kernel_name = 'parallel_sum__grouped_kv_mqa__dense_activation_mish__prompt'

def setup_inputs():

    _w = (lambda a: (lambda t: t.to(torch.bfloat16) if t.is_floating_point() else t)(torch.as_tensor(a)))
    def _A_setup():
        B, S, D, H = 1, 2048, 512, 32
        Dh = D // H
        return {
            "x": _w((lambda *s: torch.randn(*s, dtype=torch.bfloat16) * 0.05)(B, S, D)),
            "wq": _w((lambda *s: torch.randn(*s, dtype=torch.bfloat16) * 0.05)(D, H * Dh)),
            "wk": _w((lambda *s: torch.randn(*s, dtype=torch.bfloat16) * 0.05)(D, Dh)),
            "wv": _w((lambda *s: torch.randn(*s, dtype=torch.bfloat16) * 0.05)(D, Dh)),
            "wo": _w((lambda *s: torch.randn(*s, dtype=torch.bfloat16) * 0.05)(H * Dh, D)),
        }
    _A_in = _A_setup()

    def _B_setup():
        B, S, D, F = 1, 2048, 512, 1792
        return {
            "x": _w((lambda *s: torch.randn(*s, dtype=torch.bfloat16) * 0.05)(B, S, D)),
            "w1": _w((lambda *s: torch.randn(*s, dtype=torch.bfloat16) * 0.8)(D, F) * (D ** -0.5)),
            "b1": _w((lambda *s: torch.randn(*s, dtype=torch.bfloat16) * 0.4)(F)),
            "w2": _w((lambda *s: torch.randn(*s, dtype=torch.bfloat16) * 0.2)(F, D) * (F ** -0.5)),
        }
    _B_in = _B_setup()

    return {
        "A_x": _A_in["x"],
        "A_wq": _A_in["wq"],
        "A_wk": _A_in["wk"],
        "A_wv": _A_in["wv"],
        "A_wo": _A_in["wo"],
        "B_x": _B_in["x"],
        "B_w1": _B_in["w1"],
        "B_b1": _B_in["b1"],
        "B_w2": _B_in["w2"],
    }

def reference(A_x, A_wq, A_wk, A_wv, A_wo, B_x, B_w1, B_b1, B_w2):
    def _A_ref(x, wq, wk, wv, wo):
        B, S, D = x.shape
        H = 32
        Dh = D // H
        q = (lambda x, *d: x.permute(*d))((x @ wq).reshape(B, S, H, Dh), 0, 2, 1, 3)
        k = x @ wk
        v = x @ wv
        scores = torch.einsum("bhqd,bkd->bhqk", q, k) * (Dh ** -0.5)
        p = _softmax(scores, axis=-1)
        o = torch.einsum("bhqk,bkd->bhqd", p, v)
        return (lambda x, *d: x.permute(*d))(o, 0, 2, 1, 3).reshape(B, S, H * Dh) @ wo

    def _B_ref(x, w1, b1, w2):
        h = torch.einsum("bsd,df->bsf", x, w1) + b1
        sp = torch.log1p(torch.exp(-torch.abs(h))) + torch.where(h > 0, h, torch.zeros_like(h))
        act = h * torch.tanh(sp)
        return torch.einsum("bsf,fd->bsd", act, w2)

    x = A_x
    xn = _layernorm(x, axis=-1)
    return x + _A_ref(xn, A_wq, A_wk, A_wv, A_wo) + _B_ref(xn, B_w1, B_b1, B_w2)
```

```cpp
#include <cuda_runtime.h>
#include <cuda_bf16.h>
#include <cuda.h>
#include <stdint.h>

namespace {

constexpr int D_ = 512, F_ = 1792;
constexpr int NCTA = 128;

#define G1DEPTH 4
#define G2DEPTH 2
#define XFIRST 1
#define QLATE 2
#define QTHR 0
#define RING_NS 0
#define LAZY_NS 0
#define GUN1 7
#define GUN2 4
constexpr int kGun1 = GUN1, kGun2 = GUN2;
#define WG_PERM 0x3210
#define WQ1 8
#define W1GATE 0
#define W1PF 1
#define SINGLEP 0
#define POLY_MASK 0x6D75u
#define POLY_MASK2 POLY_MASK
#define REG_ATT 192
#define REG_GEMM 104
#define REG_PROD 24
static_assert(2 * REG_ATT + REG_GEMM + REG_PROD <= 512, "register pool");

constexpr uint32_t OFF_XA  = 0;
constexpr uint32_t OFF_BR  = 65536;
constexpr uint32_t OFF_ACT = OFF_BR + 65536;
constexpr uint32_t OFF_KV  = OFF_ACT + 57344;
constexpr uint32_t OFF_WKV = OFF_KV + 30720;
constexpr uint32_t OFF_B1  = OFF_WKV + 8192;
constexpr uint32_t OFF_KVO = OFF_B1 + 1792;
constexpr uint32_t OFF_BAR = OFF_KVO + 1024;
constexpr uint32_t SMEM_BYTES = OFF_BAR + 640 + 1024;
static_assert(SMEM_BYTES <= 232448, "smem");
constexpr uint32_t KV_SLOT = 10240;

enum : uint32_t {
  B_BFULL = 0, B_QFULL = 4, B_KVFULL = 12, B_OFULL = 15,
  B_BEMPTY = 21, B_KVEMPTY = 25, B_QDONE = 28,
  B_OOWN = 33, B_LAST = 35, B_ACTOWN = 36, B_ACTT = 37, B_KVRDY = 41, B_KVMMA = 42, B_EPOCH = 44, B_COUNT = 45
};
constexpr uint32_t OFF_MISC = OFF_BAR + 8 * 46;

struct __align__(1024) Scratch {
  uint4    kv[16 * 512];
  uint2    kvflag[NCTA * 4];
  uint32_t oflag[NCTA * 2 * 8];
  uint32_t actflag[NCTA * 8];
  __align__(32) uint32_t epoch;
  uint32_t pad[255];
  uint4    ex[NCTA * 9 * 512];
};
__device__ Scratch g_s;
#define g_kv g_s.kv
#define g_kvflag g_s.kvflag
#define g_oflag g_s.oflag
#define g_actflag g_s.actflag
#define g_epoch g_s.epoch
#define PROF_MARK(i) do {} while (0)

#define WG_FENCE()  asm volatile("wgmma.fence.sync.aligned;" ::: "memory")
#define WG_COMMIT() asm volatile("wgmma.commit_group.sync.aligned;" ::: "memory")
#define WG_WAIT(n)  asm volatile("wgmma.wait_group.sync.aligned %0;" ::"n"(n) : "memory")

__device__ __forceinline__ void wgmma_ss_n8_tb(float (&d)[4], uint64_t da, uint64_t db, int sd) {
  asm volatile("{.reg .pred p; setp.ne.b32 p, %6, 0;\n"
      "wgmma.mma_async.sync.aligned.m64n8k16.f32.bf16.bf16 {"
      "%0, %1, %2, %3"
      "}, %4, %5, p, 1, 1, 0, 1;}\n"
      : "+f"(d[0]), "+f"(d[1]), "+f"(d[2]), "+f"(d[3])
      : "l"(da), "l"(db), "r"(sd));
}
__device__ __forceinline__ void wgmma_ss_n64_tb(float (&d)[32], uint64_t da, uint64_t db, int sd) {
  asm volatile("{.reg .pred p; setp.ne.b32 p, %34, 0;\n"
      "wgmma.mma_async.sync.aligned.m64n64k16.f32.bf16.bf16 {"
      "%0, %1, %2, %3, %4, %5, %6, %7, %8, %9, %10, %11, %12, %13, %14, %15,"
      "%16, %17, %18, %19, %20, %21, %22, %23, %24, %25, %26, %27, %28, %29, %30, %31"
      "}, %32, %33, p, 1, 1, 0, 1;}\n"
      : "+f"(d[0]), "+f"(d[1]), "+f"(d[2]), "+f"(d[3]), "+f"(d[4]), "+f"(d[5]), "+f"(d[6]), "+f"(d[7]),
        "+f"(d[8]), "+f"(d[9]), "+f"(d[10]), "+f"(d[11]), "+f"(d[12]), "+f"(d[13]), "+f"(d[14]), "+f"(d[15]),
        "+f"(d[16]), "+f"(d[17]), "+f"(d[18]), "+f"(d[19]), "+f"(d[20]), "+f"(d[21]), "+f"(d[22]), "+f"(d[23]),
        "+f"(d[24]), "+f"(d[25]), "+f"(d[26]), "+f"(d[27]), "+f"(d[28]), "+f"(d[29]), "+f"(d[30]), "+f"(d[31])
      : "l"(da), "l"(db), "r"(sd));
}
__device__ __forceinline__ void wgmma_ss_n128_tb(float (&d)[64], uint64_t da, uint64_t db, int sd) {
  asm volatile("{.reg .pred p; setp.ne.b32 p, %66, 0;\n"
      "wgmma.mma_async.sync.aligned.m64n128k16.f32.bf16.bf16 {"
      "%0, %1, %2, %3, %4, %5, %6, %7, %8, %9, %10, %11, %12, %13, %14, %15,"
      "%16, %17, %18, %19, %20, %21, %22, %23, %24, %25, %26, %27, %28, %29, %30, %31,"
      "%32, %33, %34, %35, %36, %37, %38, %39, %40, %41, %42, %43, %44, %45, %46, %47,"
      "%48, %49, %50, %51, %52, %53, %54, %55, %56, %57, %58, %59, %60, %61, %62, %63"
      "}, %64, %65, p, 1, 1, 0, 1;}\n"
      : "+f"(d[0]), "+f"(d[1]), "+f"(d[2]), "+f"(d[3]), "+f"(d[4]), "+f"(d[5]), "+f"(d[6]), "+f"(d[7]),
        "+f"(d[8]), "+f"(d[9]), "+f"(d[10]), "+f"(d[11]), "+f"(d[12]), "+f"(d[13]), "+f"(d[14]), "+f"(d[15]),
        "+f"(d[16]), "+f"(d[17]), "+f"(d[18]), "+f"(d[19]), "+f"(d[20]), "+f"(d[21]), "+f"(d[22]), "+f"(d[23]),
        "+f"(d[24]), "+f"(d[25]), "+f"(d[26]), "+f"(d[27]), "+f"(d[28]), "+f"(d[29]), "+f"(d[30]), "+f"(d[31]),
        "+f"(d[32]), "+f"(d[33]), "+f"(d[34]), "+f"(d[35]), "+f"(d[36]), "+f"(d[37]), "+f"(d[38]), "+f"(d[39]),
        "+f"(d[40]), "+f"(d[41]), "+f"(d[42]), "+f"(d[43]), "+f"(d[44]), "+f"(d[45]), "+f"(d[46]), "+f"(d[47]),
        "+f"(d[48]), "+f"(d[49]), "+f"(d[50]), "+f"(d[51]), "+f"(d[52]), "+f"(d[53]), "+f"(d[54]), "+f"(d[55]),
        "+f"(d[56]), "+f"(d[57]), "+f"(d[58]), "+f"(d[59]), "+f"(d[60]), "+f"(d[61]), "+f"(d[62]), "+f"(d[63])
      : "l"(da), "l"(db), "r"(sd));
}
__device__ __forceinline__ void wgmma_rs_n64(float (&d)[32], uint32_t a0, uint32_t a1, uint32_t a2, uint32_t a3, uint64_t db, int sd) {
  asm volatile("{.reg .pred p; setp.ne.b32 p, %37, 0;\n"
      "wgmma.mma_async.sync.aligned.m64n64k16.f32.bf16.bf16 {"
      "%0, %1, %2, %3, %4, %5, %6, %7, %8, %9, %10, %11, %12, %13, %14, %15,"
      "%16, %17, %18, %19, %20, %21, %22, %23, %24, %25, %26, %27, %28, %29, %30, %31"
      "}, {%32,%33,%34,%35}, %36, p, 1, 1, 0;}\n"
      : "+f"(d[0]), "+f"(d[1]), "+f"(d[2]), "+f"(d[3]), "+f"(d[4]), "+f"(d[5]), "+f"(d[6]), "+f"(d[7]),
        "+f"(d[8]), "+f"(d[9]), "+f"(d[10]), "+f"(d[11]), "+f"(d[12]), "+f"(d[13]), "+f"(d[14]), "+f"(d[15]),
        "+f"(d[16]), "+f"(d[17]), "+f"(d[18]), "+f"(d[19]), "+f"(d[20]), "+f"(d[21]), "+f"(d[22]), "+f"(d[23]),
        "+f"(d[24]), "+f"(d[25]), "+f"(d[26]), "+f"(d[27]), "+f"(d[28]), "+f"(d[29]), "+f"(d[30]), "+f"(d[31])
      : "r"(a0), "r"(a1), "r"(a2), "r"(a3), "l"(db), "r"(sd));
}
__device__ __forceinline__ void wgmma_rs_n24_tb(float (&d)[12], uint32_t a0, uint32_t a1, uint32_t a2, uint32_t a3, uint64_t db, int sd) {
  asm volatile("{.reg .pred p; setp.ne.b32 p, %17, 0;\n"
      "wgmma.mma_async.sync.aligned.m64n24k16.f32.bf16.bf16 {"
      "%0, %1, %2, %3, %4, %5, %6, %7, %8, %9, %10, %11"
      "}, {%12,%13,%14,%15}, %16, p, 1, 1, 1;}\n"
      : "+f"(d[0]), "+f"(d[1]), "+f"(d[2]), "+f"(d[3]), "+f"(d[4]), "+f"(d[5]), "+f"(d[6]), "+f"(d[7]),
        "+f"(d[8]), "+f"(d[9]), "+f"(d[10]), "+f"(d[11])
      : "r"(a0), "r"(a1), "r"(a2), "r"(a3), "l"(db), "r"(sd));
}

template <int N> __device__ __forceinline__ void fence_regs(float (&a)[N]) {
#pragma unroll
  for (int i = 0; i < N; i++) asm volatile("" : "+f"(a[i])::"memory");
}
template <int N> __device__ __forceinline__ void fence_regs(uint32_t (&a)[N]) {
#pragma unroll
  for (int i = 0; i < N; i++) asm volatile("" : "+r"(a[i])::"memory");
}
__host__ __device__ constexpr uint64_t mkdesc(uint32_t addr, uint32_t lbo, uint32_t sbo, uint32_t swz) {
  return (uint64_t)((addr & 0x3FFFF) >> 4) | ((uint64_t)(lbo >> 4) << 16) | ((uint64_t)(sbo >> 4) << 32) | ((uint64_t)swz << 62);
}
__host__ __device__ constexpr uint64_t desc_a(uint32_t addr) { return mkdesc(addr, 16, 1024, 1); }
__host__ __device__ constexpr uint64_t desc_b(uint32_t addr) { return mkdesc(addr, 8192, 1024, 1); }

__device__ __forceinline__ void mbar_init(uint32_t bar, uint32_t cnt) {
  asm volatile("mbarrier.init.shared::cta.b64 [%0], %1;" ::"r"(bar), "r"(cnt) : "memory");
}
__device__ __forceinline__ void warp_arrive(uint32_t bar, uint32_t n = 1) {
  asm volatile("{.reg .pred p; elect.sync _|p, 0xffffffff; @p mbarrier.arrive.shared::cta.b64 _, [%0], %1;}" ::"r"(bar), "r"(n) : "memory");
}
__device__ __forceinline__ void mbar_expect(uint32_t bar, uint32_t bytes) {
  asm volatile("mbarrier.arrive.expect_tx.shared::cta.b64 _, [%0], %1;" ::"r"(bar), "r"(bytes) : "memory");
}
__device__ __forceinline__ void mbar_wait(uint32_t bar, uint32_t parity) {
  asm volatile(
      "{.reg .pred p; .reg .u32 c;\n"
      "mbarrier.try_wait.parity.shared::cta.b64 p, [%0], %1;\n"
      "@p bra DONE;\n"
      "mov.u32 c, 0;\n"
      "LOOP:\n"
      "mbarrier.try_wait.parity.shared::cta.b64 p, [%0], %1;\n"
      "@p bra DONE;\n"
      "add.u32 c, c, 1;\n"
      "setp.lt.u32 p, c, 4000000;\n"
      "@p bra LOOP;\n"
      "trap;\n"
      "DONE:\n"
      "}\n" ::"r"(bar), "r"(parity) : "memory");
}
template <int NS> __device__ __forceinline__ void mbar_wait_lazy(uint32_t bar, uint32_t parity) {
  if (NS == 0) { mbar_wait(bar, parity); return; }
  asm volatile(
      "{.reg .pred p; .reg .u32 c;\n"
      "mov.u32 c, 0;\n"
      "LOOP:\n"
      "mbarrier.test_wait.parity.shared::cta.b64 p, [%0], %1;\n"
      "@p bra DONE;\n"
      "nanosleep.u32 %2;\n"
      "add.u32 c, c, 1;\n"
      "setp.lt.u32 p, c, 4000000;\n"
      "@p bra LOOP;\n"
      "trap;\n"
      "DONE:\n"
      "}\n" ::"r"(bar), "r"(parity), "n"(NS) : "memory");
}
__device__ __forceinline__ void warp_tma(uint32_t dst, const CUtensorMap* map, int row, int grp, uint32_t bar) {
  asm volatile("{.reg .pred p; elect.sync _|p, 0xffffffff;\n"
               "@p mbarrier.arrive.expect_tx.shared::cta.b64 _, [%2], 16384;\n"
               "@p cp.async.bulk.tensor.3d.shared::cluster.global.mbarrier::complete_tx::bytes [%0], [%1, {%5, %3, %4}], [%2];}"
               ::"r"(dst), "l"(map), "r"(bar), "r"(row), "r"(grp), "r"(0) : "memory");
}
__device__ __forceinline__ void warp_tma_ab(uint32_t dst, const CUtensorMap* map, int row, int grp, uint32_t bar, uint32_t dsta, const void* srca) {
  asm volatile("{.reg .pred p; elect.sync _|p, 0xffffffff;\n"
               "@p mbarrier.arrive.expect_tx.shared::cta.b64 _, [%2], 24576;\n"
               "@p cp.async.bulk.shared::cluster.global.mbarrier::complete_tx::bytes [%6], [%7], 8192, [%2];\n"
               "@p cp.async.bulk.tensor.3d.shared::cluster.global.mbarrier::complete_tx::bytes [%0], [%1, {%5, %3, %4}], [%2];}"
               ::"r"(dst), "l"(map), "r"(bar), "r"(row), "r"(grp), "r"(0), "r"(dsta), "l"(srca) : "memory");
}
__device__ __forceinline__ void warp_bulk_load(uint32_t dst, const void* src, uint32_t bar) {
  asm volatile("{.reg .pred p; elect.sync _|p, 0xffffffff;\n"
               "@p mbarrier.arrive.expect_tx.shared::cta.b64 _, [%2], 8192;\n"
               "@p cp.async.bulk.shared::cluster.global.mbarrier::complete_tx::bytes [%0], [%1], 8192, [%2];}"
               ::"r"(dst), "l"(src), "r"(bar) : "memory");
}
__device__ __forceinline__ void warp_bulk_store(void* dst, uint32_t src, uint32_t bytes) {
  asm volatile("{.reg .pred p; elect.sync _|p, 0xffffffff;\n"
               "@p cp.async.bulk.global.shared::cta.bulk_group [%0], [%1], %2;\n"
               "@p cp.async.bulk.commit_group;}" ::"l"(dst), "r"(src), "r"(bytes) : "memory");
}
__device__ __forceinline__ void warp_publish(void* flag, uint32_t v0, uint32_t v1) {
  asm volatile("{.reg .pred p; elect.sync _|p, 0xffffffff;\n"
               "cp.async.bulk.wait_group 0;\n"
               "@p st.relaxed.gpu.global.v2.u32 [%0], {%1,%2};}" ::"l"(flag), "r"(v0), "r"(v1) : "memory");
}
__device__ __forceinline__ void bulk_load(uint32_t dst, const void* src, uint32_t bytes, uint32_t bar) {
  asm volatile("cp.async.bulk.shared::cluster.global.mbarrier::complete_tx::bytes [%0], [%1], %2, [%3];"
               ::"r"(dst), "l"(src), "r"(bytes), "r"(bar) : "memory");
}
__device__ __forceinline__ void bulk_store(void* dst, uint32_t src, uint32_t bytes) {
  asm volatile("cp.async.bulk.global.shared::cta.bulk_group [%0], [%1], %2;" ::"l"(dst), "r"(src), "r"(bytes) : "memory");
}
__device__ __forceinline__ void bulk_commit() { asm volatile("cp.async.bulk.commit_group;" ::: "memory"); }
__device__ __forceinline__ void bulk_wait_all() { asm volatile("cp.async.bulk.wait_group 0;" ::: "memory"); }
__device__ __forceinline__ void l2_prefetch(const void* p, uint32_t bytes) {
  asm volatile("cp.async.bulk.prefetch.L2.global [%0], %1;" ::"l"(p), "r"(bytes) : "memory");
}
__device__ __forceinline__ void fence_async_smem() { asm volatile("fence.proxy.async.shared::cta;" ::: "memory"); }
__device__ __forceinline__ void fence_async_gmem() { asm volatile("fence.proxy.async.global;" ::: "memory"); }
__device__ __forceinline__ void bar_sync(int id, int n) { asm volatile("bar.sync %0, %1;" ::"r"(id), "r"(n) : "memory"); }
__device__ __forceinline__ void st_flag(uint32_t* p, uint32_t v) {
  asm volatile("st.relaxed.gpu.global.u32 [%0], %1;" ::"l"(p), "r"(v) : "memory");
}
__device__ __forceinline__ uint32_t ld_flag(const uint32_t* p) {
  uint32_t v;
  asm volatile("ld.relaxed.gpu.global.u32 %0, [%1];" : "=r"(v) : "l"(p) : "memory");
  return v;
}
__device__ __forceinline__ void poll_flag(const uint32_t* p, uint32_t want) {
  uint32_t n = 0;
  while (ld_flag(p) != want)
    if (++n > 4000000u) __trap();
}
__device__ __forceinline__ void stsm_x4(uint32_t addr, uint32_t r0, uint32_t r1, uint32_t r2, uint32_t r3) {
  asm volatile("stmatrix.sync.aligned.m8n8.x4.shared.b16 [%0], {%1,%2,%3,%4};" ::"r"(addr), "r"(r0), "r"(r1), "r"(r2), "r"(r3) : "memory");
}
__device__ __forceinline__ void sts128(uint32_t addr, uint32_t r0, uint32_t r1, uint32_t r2, uint32_t r3) {
  asm volatile("st.shared.v4.u32 [%0], {%1,%2,%3,%4};" ::"r"(addr), "r"(r0), "r"(r1), "r"(r2), "r"(r3) : "memory");
}
__device__ __forceinline__ float ex2(float x) { float y; asm("ex2.approx.ftz.f32 %0, %1;" : "=f"(y) : "f"(x)); return y; }
__device__ __forceinline__ float rcp(float x) { float y; asm("rcp.approx.ftz.f32 %0, %1;" : "=f"(y) : "f"(x)); return y; }
__device__ __forceinline__ uint32_t pack_bf16(float lo, float hi) {
  uint32_t y; asm("cvt.rn.bf16x2.f32 %0, %1, %2;" : "=r"(y) : "f"(hi), "f"(lo)); return y;
}
__device__ __forceinline__ float bf_lo(uint32_t v) { return __uint_as_float(v << 16); }
__device__ __forceinline__ float bf_hi(uint32_t v) { return __uint_as_float(v & 0xFFFF0000u); }
__device__ __forceinline__ uint32_t hfma2bf(uint32_t a, uint32_t b, uint32_t c) {
  uint32_t d; asm("fma.rn.bf16x2 %0, %1, %2, %3;" : "=r"(d) : "r"(a), "r"(b), "r"(c)); return d;
}
__device__ __forceinline__ uint32_t exp2_pair_fma(float a, float b) {
  const float M = 98304.f + 127.f;
  uint32_t x = __byte_perm(__float_as_uint(a + M), __float_as_uint(b + M), 0x5410);
  uint32_t y, r;
  asm("lop3.b32 %0, %1, 0x007F007F, %2, 0xEA;" : "=r"(y) : "r"(x), "r"(0x3F803F80u));
  uint32_t h = hfma2bf(hfma2bf(y, 0x3EAF3EAFu, 0xBD09BD09u), y, 0x3F323F32u);
  asm("lop3.b32 %0, %1, 0x007F007F, %2, 0xB8;" : "=r"(r) : "r"(x), "r"(h));
  return r;
}

#define PACKSCHED 0
template <int PEND, bool FIRST, uint32_t MASK>
__device__ __forceinline__ void attn_step(float (&s)[32], uint32_t (&p)[16], float (&o)[12], uint64_t dv) {
#pragma unroll
  for (int c = 0; c < 4; c++) {
    if (!FIRST && (SINGLEP || c == 0)) WG_WAIT(PEND);
    if (c == 0) fence_regs(s);
#pragma unroll
    for (int i = 4 * c; i < 4 * c + 4; i++)
      p[i] = ((MASK >> i) & 1) ? exp2_pair_fma(s[2 * i], s[2 * i + 1]) : pack_bf16(ex2(s[2 * i]), ex2(s[2 * i + 1]));
#pragma unroll
    for (int i = 4 * c; i < 4 * c + 4; i++) asm volatile("" : "+r"(p[i])::"memory");
    WG_FENCE();
    wgmma_rs_n24_tb(o, p[4 * c], p[4 * c + 1], p[4 * c + 2], p[4 * c + 3], dv + c * 16, 1);
    WG_COMMIT();
  }
}

struct Params {
  const __nv_bfloat16 *x, *wq, *wk, *wv, *b1, *w1, *w2, *wo;
  __nv_bfloat16* out;
};

#define GEMM_CHUNK(GDEPTH, WGMMA, ACC, DA, DB, FIRST, REL_PREV)                              \
  do {                                                                                       \
    const uint64_t da_ = (DA), db_ = (DB);                                                   \
    WG_FENCE();                                                                              \
    _Pragma("unroll") for (int kk = 0; kk < 4; kk++) {                                       \
      WGMMA(ACC, da_ + kk * 2, db_ + kk * 128, !((FIRST) && kk == 0));                       \
      if (GDEPTH == 1) { WG_COMMIT(); WG_WAIT(0); if (kk == 0) { REL_PREV; } }               \
      if (GDEPTH == 5 && (kk & 1)) { WG_COMMIT(); WG_WAIT(0); if (kk == 1) { REL_PREV; } }   \
      if (GDEPTH == 2) { WG_COMMIT(); WG_WAIT(1); if (kk == 0) { REL_PREV; } }               \
      if (GDEPTH == 3 && (kk & 1)) { WG_COMMIT(); WG_WAIT(1); if (kk == 1) { REL_PREV; } }   \
    }                                                                                        \
    if (GDEPTH == 4) { WG_COMMIT(); WG_WAIT(1); REL_PREV; }                                  \
  } while (0)

__global__ void __launch_bounds__(512, 1)
fused_kernel(const __grid_constant__ CUtensorMap map_wq, const __grid_constant__ CUtensorMap map_w1,
             const __grid_constant__ CUtensorMap map_w1t, const __grid_constant__ CUtensorMap map_w2,
             const __grid_constant__ CUtensorMap map_wo, const Params prm) {
  extern __shared__ uint8_t smem_raw[];
  constexpr uint32_t sb = 1024, bars = sb + OFF_BAR;
  if ((uint32_t)__cvta_generic_to_shared(smem_raw) > sb) __trap();
  const int lane = threadIdx.x & 31;
  const int warp = __shfl_sync(0xffffffffu, ((WG_PERM >> ((threadIdx.x >> 7) * 4)) & 3) * 4 + ((threadIdx.x >> 5) & 3), 0);
  const int tid = warp * 32 + lane;
  const int rb = blockIdx.x >> 2, j = blockIdx.x & 3;

  if (warp == 0) {
    if (lane == 0) {
      l2_prefetch(reinterpret_cast<const uint8_t*>(prm.wq) + blockIdx.x * 4096, 4096);
#pragma unroll
      for (int i = 0; i < 8; i++) mbar_init(bars + 8 * i, 1);
      mbar_init(bars + 8 * B_EPOCH, 1);
      asm volatile("fence.mbarrier_init.release.cluster;" ::: "memory");
      mbar_expect(bars + 8 * B_EPOCH, 16);
      bulk_load(sb + OFF_MISC, &g_epoch, 16, bars + 8 * B_EPOCH);
    }
    __syncwarp();
    asm volatile("bar.arrive 0, 512;" ::: "memory");
    bar_sync(4, 512);
    if (lane == 0) PROF_MARK(13);
#pragma unroll 1
    for (int c = 0; c < WQ1; c++) warp_tma(sb + OFF_BR + c * 16384, &map_wq, 64 * c, 2 * j, bars + 8 * c);
  } else {
    {
      const int uw = warp;
      if (lane == 0 && uw <= 12) {
#pragma unroll
        for (int k = 0; k < 3; k++) {
          const uint32_t i = 8 + (uw - 1) * 3 + k;
          mbar_init(bars + 8 * i, i < B_BEMPTY ? 1 : i <= B_QDONE ? 8 : 4);
        }
        asm volatile("fence.mbarrier_init.release.cluster;" ::: "memory");
      }
      __syncwarp();
    }
    uint4 v[5][2];
    const uint4* xr = reinterpret_cast<const uint4*>(prm.x + (size_t)(rb * 64) * D_) + lane;
    const bool five = warp <= 4;
#pragma unroll
    for (int r = 0; r < 4; r++) { v[r][0] = __ldg(xr + (warp * 4 + r) * 64); v[r][1] = __ldg(xr + (warp * 4 + r) * 64 + 32); }
    v[4][0] = v[4][1] = make_uint4(0, 0, 0, 0);
    if (five) { v[4][0] = __ldg(xr + (warp - 1) * 64); v[4][1] = __ldg(xr + (warp - 1) * 64 + 32); }
    if (tid == 160) PROF_MARK(26);
    const __nv_bfloat16* wsrc = (j < 2 ? prm.wk : prm.wv) + (j & 1) * 8;
    const uint4 wkv = __ldg(reinterpret_cast<const uint4*>(wsrc + tid * 16));
    uint4 wkv0 = make_uint4(0, 0, 0, 0);
    if (warp == 15) wkv0 = __ldg(reinterpret_cast<const uint4*>(wsrc + lane * 16));
    float b1v = 0.f;
    if (tid >= 64) b1v = __bfloat162float(prm.b1[448 * j + tid - 64]);
    if (tid >= 128) {
      const int t = tid - 128;
      sts128(sb + OFF_KV + (t >> 7) * KV_SLOT + 8192 + (t & 127) * 16, 0x3F803F80u, 0x3F803F80u, 0x3F803F80u, 0x3F803F80u);
    }
    float f[5][16], mu[5], rs[5];
#pragma unroll
    for (int r = 0; r < 5; r++) {
      mu[r] = rs[r] = 0.f;
      if (r < 4 || five) {
        const uint32_t w[8] = {v[r][0].x, v[r][0].y, v[r][0].z, v[r][0].w, v[r][1].x, v[r][1].y, v[r][1].z, v[r][1].w};
#pragma unroll
        for (int i = 0; i < 8; i++) {
          f[r][2 * i] = bf_lo(w[i]); f[r][2 * i + 1] = bf_hi(w[i]);
          mu[r] += f[r][2 * i]; rs[r] = fmaf(f[r][2 * i], f[r][2 * i], rs[r]);
          mu[r] += f[r][2 * i + 1]; rs[r] = fmaf(f[r][2 * i + 1], f[r][2 * i + 1], rs[r]);
        }
      }
    }
    asm volatile("bar.arrive 4, 512;" ::"f"(mu[0]), "f"(mu[1]), "f"(mu[2]), "f"(mu[3]), "f"(mu[4]) : "memory");
#pragma unroll
    for (int o = 16; o; o >>= 1)
#pragma unroll
      for (int r = 0; r < 5; r++) { mu[r] += __shfl_xor_sync(0xffffffffu, mu[r], o); rs[r] += __shfl_xor_sync(0xffffffffu, rs[r], o); }
    if (tid == 160) PROF_MARK(14);
#pragma unroll
    for (int r = 0; r < 5; r++) {
      if (r < 4 || five) {
        const float m = mu[r] * (1.f / D_);
        const float k = rsqrtf(fmaxf(fmaf(-m, m, rs[r] * (1.f / D_)), 0.f) + 1e-5f), c = -m * k;
        const int row = r < 4 ? warp * 4 + r : warp - 1;
#pragma unroll
        for (int h = 0; h < 2; h++) {
          const uint32_t a = sb + OFF_XA + (h * 4 + (lane >> 3)) * 8192 + row * 128 + (((lane & 7) ^ (row & 7)) << 4);
          sts128(a, pack_bf16(fmaf(f[r][8 * h], k, c), fmaf(f[r][8 * h + 1], k, c)), pack_bf16(fmaf(f[r][8 * h + 2], k, c), fmaf(f[r][8 * h + 3], k, c)),
                 pack_bf16(fmaf(f[r][8 * h + 4], k, c), fmaf(f[r][8 * h + 5], k, c)), pack_bf16(fmaf(f[r][8 * h + 6], k, c), fmaf(f[r][8 * h + 7], k, c)));
        }
      }
    }
    sts128(sb + OFF_WKV + tid * 16, wkv.x, wkv.y, wkv.z, wkv.w);
    if (warp == 15) sts128(sb + OFF_WKV + lane * 16, wkv0.x, wkv0.y, wkv0.z, wkv0.w);
    if (tid >= 64) asm volatile("st.shared.f32 [%0], %1;" ::"r"(sb + OFF_B1 + (tid - 64) * 4), "f"(b1v) : "memory");
    if (tid == 160) PROF_MARK(15);
    fence_async_smem();
    bar_sync(0, 512);
  }
  auto get_epoch = [&]() {
    uint32_t e;
    mbar_wait(bars + 8 * B_EPOCH, 0);
    asm volatile("ld.shared.u32 %0, [%1];" : "=r"(e) : "r"(sb + OFF_MISC) : "memory");
    return e + 1;
  };
  const int wg = warp >> 2, wq = warp & 3;
  if (tid == 160) PROF_MARK(0);

  if (wg == 0) {
    asm volatile("setmaxnreg.dec.sync.aligned.u32 %0;" ::"n"(REG_PROD));
    if (warp == 0) {
      if (WQ1 < 8) mbar_wait(bars + 8 * B_KVRDY, 0);
#pragma unroll 1
      for (int c = WQ1; c < 8; c++) warp_tma(sb + OFF_BR + c * 16384, &map_wq, 64 * c, 2 * j, bars + 8 * c);
      if (lane == 0) PROF_MARK(12);
    }
    if (warp == 0 || warp == 3) {
      const int odd = warp & 1;
      uint32_t st = odd;
#define RING_WAIT() mbar_wait_lazy<RING_NS>(bars + 8 * B_BEMPTY + 8 * (st & 3), (st >> 2) & 1)
#define RING(MAP, ROW, GRP) do { RING_WAIT(); warp_tma(sb + OFF_BR + (st & 3) * 16384, MAP, ROW, GRP, bars + 8 * B_BFULL + 8 * (st & 3)); st += 2; } while (0)
#pragma unroll 1
      for (int i = odd; i < 24; i += 2) RING(&map_w1, 64 * (i & 7), 7 * j + 2 * (i >> 3));
#pragma unroll 1
      for (int i = odd; i < 4; i += 2) RING(&map_w1t, 128 * i, 7 * j + 6);
#pragma unroll 1
      for (int u = odd; u < 7; u += 2) RING(&map_w2, 448 * j + 64 * u, 2 * j);
      const uint32_t epoch = get_epoch();
      int c = odd ^ 1;
#pragma unroll 1
      for (int q = 1; q < 4; q++) {
        const int jj = (j + q) & 3;
        poll_flag(g_actflag + (rb * 4 + jj) * 8, epoch);
        fence_async_gmem();
#pragma unroll 1
        for (; c < 7; c += 2) {
          RING_WAIT();
          warp_tma_ab(sb + OFF_BR + (st & 3) * 16384, &map_w2, 448 * jj + 64 * c, 2 * j, bars + 8 * B_BFULL + 8 * (st & 3),
                      sb + OFF_XA + (st & 3) * 8192, g_s.ex + ((rb * 4 + jj) * 9 + c) * 512);
          st += 2;
        }
        c -= 7;
      }
#pragma unroll 1
      for (int u = odd; u < 4; u += 2) RING(&map_wo, (128 * j + 64 * u) & 511, 2 * j);
      if (odd) {
        warp_tma(sb + OFF_XA, &map_wo, (128 * j + 256) & 511, 2 * j, bars + 8 * B_QFULL);
        warp_tma(sb + OFF_XA + 16384, &map_wo, (128 * j + 320) & 511, 2 * j, bars + 8 * (B_QFULL + 1));
      }
      mbar_wait(bars + 8 * B_BEMPTY + 8 * odd, 1);
      warp_tma(sb + OFF_BR + odd * 16384, &map_wo, (128 * j + 384 + 64 * odd) & 511, 2 * j, bars + 8 * B_BFULL + 8 * odd);
    } else if (warp == 1) {
      const uint32_t epoch = get_epoch();
      float kmax;
      for (uint32_t n = 0;; n++) {
        bool ok = true;
        kmax = 0.f;
#pragma unroll
        for (int i = 0; i < 4; i++) {
          uint32_t e, v;
          asm volatile("ld.relaxed.gpu.global.v2.u32 {%0,%1}, [%2];" : "=r"(e), "=r"(v) : "l"(g_kvflag + (lane + 32 * i) * 4) : "memory");
          ok &= e == epoch;
          const float t = __uint_as_float(v) + __shfl_down_sync(0xffffffffu, __uint_as_float(v), 1);
          if ((lane & 3) == 0) asm("max.NaN.f32 %0, %1, %2;" : "=f"(kmax) : "f"(kmax), "f"(t));
        }
        if (__all_sync(0xffffffffu, ok)) break;
        if (n > 4000000u) __trap();
      }
#pragma unroll
      for (int o = 16; o; o >>= 1) {
        const float t = __shfl_xor_sync(0xffffffffu, kmax, o);
        asm("max.NaN.f32 %0, %1, %2;" : "=f"(kmax) : "f"(kmax), "f"(t));
      }
      if (lane == 0) {
        PROF_MARK(1);
        asm volatile("st.shared.f32 [%0], %1;" ::"r"(sb + OFF_MISC + 32), "f"(kmax) : "memory");
      }
      fence_async_gmem();
      __syncwarp();
      uint32_t slot = 1, par = 1;
#pragma unroll 1
      for (int i = 0; i < 16; i++) {
        if (i == 2) {
          mbar_wait(bars + 8 * B_QDONE, 0);
        }
        if (i >= 3) mbar_wait_lazy<LAZY_NS>(bars + 8 * B_KVEMPTY + 8 * slot, par);
        if (i == 15) warp_arrive(bars + 8 * B_LAST, 4);
        warp_bulk_load(sb + OFF_KV + slot * KV_SLOT, g_kv + ((i + (rb >> 1)) & 15) * 512, bars + 8 * B_KVFULL + 8 * slot);
        if (++slot == 3) slot = 0;
        if (slot == 1) par ^= 1;
      }
      if (blockIdx.x == 0 && lane == 0) st_flag(&g_epoch, epoch);
    } else if (warp == 2) {
      const uint32_t epoch = get_epoch();
      if (lane == 0) l2_prefetch(reinterpret_cast<const uint8_t*>(prm.w1) + blockIdx.x * 14336, 14336);
      mbar_wait(bars + 8 * B_QDONE, 0);
      if (lane == 0) {
        l2_prefetch(reinterpret_cast<const uint8_t*>(prm.w2) + blockIdx.x * 14336, 14336);
        l2_prefetch(reinterpret_cast<const uint8_t*>(prm.wo) + blockIdx.x * 4096, 4096);
      }
      __syncwarp();
#pragma unroll 1
      for (int t = 0; t < 4; t++) {
        mbar_wait_lazy<LAZY_NS>(bars + 8 * B_ACTT + 8 * t, 0);
        warp_bulk_store(g_s.ex + (blockIdx.x * 9 + 2 * t) * 512, sb + OFF_ACT + 2 * t * 8192, t < 3 ? 16384 : 8192);
      }
      warp_publish(g_actflag + blockIdx.x * 8, epoch, 0);
      mbar_wait_lazy<LAZY_NS>(bars + 8 * B_ACTOWN, 0);
      mbar_wait_lazy<LAZY_NS>(bars + 8 * B_LAST, 0);
      if (lane == 0) PROF_MARK(25);
      if (lane < 6) {
        const int src = rb * 4 + ((j + 1 + (lane >> 1)) & 3);
        for (uint32_t n = 0, done = 0; !done; n++) {
          if (ld_flag(g_oflag + (src * 2 + (lane & 1)) * 8) == epoch) {
            fence_async_gmem();
            mbar_expect(bars + 8 * (B_OFULL + lane), 8192);
            bulk_load(sb + OFF_ACT + lane * 8192, g_s.ex + (src * 9 + 7 + (lane & 1)) * 512, 8192, bars + 8 * (B_OFULL + lane));
            done = 1;
          }
          if (n > 4000000u) __trap();
        }
        if (lane == 5) PROF_MARK(2);
      }
    }
  } else if (wg == 1) {
    asm volatile("setmaxnreg.dec.sync.aligned.u32 %0;" ::"n"(REG_GEMM));
    const int g = lane >> 2, t4 = lane & 3;
    {
      float kv[4] = {0.f, 0.f, 0.f, 0.f};
      fence_regs(kv);
      const uint64_t da = desc_a(sb + OFF_XA), db = mkdesc(sb + OFF_WKV, 128, 128, 0);
#pragma unroll 1
      for (int c = 0; c < 8; c++) {
        WG_FENCE();
#pragma unroll
        for (int kk = 0; kk < 4; kk++) wgmma_ss_n8_tb(kv, da + c * 512 + kk * 2, db + c * 64 + kk * 16, 1);
        WG_COMMIT();
      }
      if (tid == 128) PROF_MARK(17);
      WG_WAIT(0);
      fence_regs(kv);
      if (tid == 128) PROF_MARK(18);
      const uint32_t p0 = pack_bf16(kv[0], kv[1]), p1 = pack_bf16(kv[2], kv[3]);
      asm volatile("st.shared.u32 [%0], %1;" ::"r"(sb + OFF_KVO + (wq * 16 + g) * 16 + t4 * 4), "r"(p0) : "memory");
      asm volatile("st.shared.u32 [%0], %1;" ::"r"(sb + OFF_KVO + (wq * 16 + g + 8) * 16 + t4 * 4), "r"(p1) : "memory");
      fence_async_smem();
      bar_sync(1, 128);
      if (wq == 0) warp_bulk_store(g_kv + (rb >> 1) * 512 + j * 128 + (rb & 1) * 64, sb + OFF_KVO, 1024);
      if (tid == 128) PROF_MARK(19);
      float n0 = bf_lo(p0) * bf_lo(p0) + bf_hi(p0) * bf_hi(p0), n1 = bf_lo(p1) * bf_lo(p1) + bf_hi(p1) * bf_hi(p1);
      n0 += __shfl_xor_sync(0xffffffffu, n0, 1); n1 += __shfl_xor_sync(0xffffffffu, n1, 1);
      n0 += __shfl_xor_sync(0xffffffffu, n0, 2); n1 += __shfl_xor_sync(0xffffffffu, n1, 2);
      asm("max.NaN.f32 %0, %1, %2;" : "=f"(n0) : "f"(n0), "f"(n1));
#pragma unroll
      for (int o = 4; o < 32; o <<= 1) {
        const float t = __shfl_xor_sync(0xffffffffu, n0, o);
        asm("max.NaN.f32 %0, %1, %2;" : "=f"(n0) : "f"(n0), "f"(t));
      }
      if (lane == 0) asm volatile("st.shared.f32 [%0], %1;" ::"r"(sb + OFF_MISC + 16 + wq * 4), "f"(n0) : "memory");
      bar_sync(1, 128);
      warp_arrive(bars + 8 * B_KVMMA);
      if (wq == 0) {
        float m0, m1, m2, m3;
        asm volatile("ld.shared.v4.f32 {%0,%1,%2,%3}, [%4];" : "=f"(m0), "=f"(m1), "=f"(m2), "=f"(m3) : "r"(sb + OFF_MISC + 16) : "memory");
        asm("max.NaN.f32 %0, %1, %2;" : "=f"(m0) : "f"(m0), "f"(m1));
        asm("max.NaN.f32 %0, %1, %2;" : "=f"(m2) : "f"(m2), "f"(m3));
        asm("max.NaN.f32 %0, %1, %2;" : "=f"(m0) : "f"(m0), "f"(m2));
        warp_publish(g_kvflag + blockIdx.x * 4, get_epoch(), __float_as_uint(m0));
      }
      if (tid == 128) PROF_MARK(3);
      warp_arrive(bars + 8 * B_KVRDY);
    }
    float acc[64];
#pragma unroll
    for (int i = 0; i < 64; i++) acc[i] = 0.f;
    const uint32_t st_row = wq * 16 + (lane & 7) + ((lane >> 3) & 1) * 8;
    const uint64_t dxa = desc_a(sb + OFF_XA), dact = desc_a(sb + OFF_ACT), dbr = desc_b(sb + OFF_BR);
#define WAIT_B(slot, par) mbar_wait(bars + 8 * B_BFULL + 8 * (slot), par)
#define REL_B(i) warp_arrive(bars + 8 * B_BEMPTY + 8 * ((i) & 3), 2)
    mbar_wait(bars + 8 * B_QDONE, 0);
#pragma unroll 1
    for (int t = 0; t < 4; t++) {
      fence_regs(acc);
      if (t < 3) {
        WAIT_B(0, 1);
        GEMM_CHUNK(G1DEPTH, wgmma_ss_n128_tb, acc, dxa, dbr, true, );
#pragma unroll kGun1
        for (uint32_t c = 1; c < 8; c++) {
          WAIT_B(c & 3, (c >> 2) ^ 1);
          GEMM_CHUNK(G1DEPTH, wgmma_ss_n128_tb, acc, dxa + c * 512, dbr + (c & 3) * 1024, false, REL_B(c - 1));
        }
      } else {
        float (&acc32)[32] = *reinterpret_cast<float (*)[32]>(&acc[0]);
#pragma unroll
        for (int i = 0; i < 32; i++) acc32[i] = 0.f;
        fence_regs(acc32);
#pragma unroll kGun1
        for (uint32_t c = 0; c < 4; c++) {
          WAIT_B(c, 1);
          GEMM_CHUNK(G1DEPTH, wgmma_ss_n64_tb, acc32, dxa + c * 1024, dbr + c * 1024, false, if (c > 0) REL_B(c - 1));
          GEMM_CHUNK(G1DEPTH, wgmma_ss_n64_tb, acc32, dxa + c * 1024 + 512, dbr + c * 1024 + 512, false, );
        }
      }
      WG_WAIT(0);
      fence_regs(acc);
      REL_B(3);
      const uint32_t b1a = sb + OFF_B1 + t * 512 + t4 * 8;
      const uint32_t sta = sb + OFF_ACT + t * 16384 + st_row * 128, stx = ((lane >> 4) ^ (st_row & 7)) << 4;
#pragma unroll
      for (int c = 0; c < 16; c += 2) {
        if (t < 3 || c < 8) {
          uint32_t r[4];
#pragma unroll
          for (int u = 0; u < 2; u++) {
            float b0, b1;
            asm volatile("ld.shared.v2.f32 {%0,%1}, [%2];" : "=f"(b0), "=f"(b1) : "r"(b1a + (c + u) * 32));
            float a[4];
#pragma unroll
            for (int e = 0; e < 4; e++) {
              const float h = acc[4 * (c + u) + e] + ((e & 1) ? b1 : b0);
              const float w = fmaf(ex2(h * 1.4426950408889634f), 0.7071067811865476f, 0.7071067811865476f);
              a[e] = fmaf(-h, rcp(fmaf(w, w, 0.5f)), h);
            }
            r[2 * u] = pack_bf16(a[0], a[1]); r[2 * u + 1] = pack_bf16(a[2], a[3]);
          }
          stsm_x4(sta + (c >> 3) * 8192 + (stx ^ ((c & 7) << 4)), r[0], r[1], r[2], r[3]);
        }
      }
      fence_async_smem();
      __syncwarp();
      warp_arrive(bars + 8 * B_ACTT + 8 * t);
    }
    if (tid == 128) PROF_MARK(4);
    {
      const uint32_t* xp = reinterpret_cast<const uint32_t*>(prm.x + (size_t)(rb * 64 + wq * 16 + g) * D_ + 128 * j) + t4;
#pragma unroll
      for (int c = 0; c < 16; c++) {
        const uint32_t a = __ldg(xp + c * 4), b = __ldg(xp + 8 * (D_ / 2) + c * 4);
        acc[4 * c] = bf_lo(a); acc[4 * c + 1] = bf_hi(a); acc[4 * c + 2] = bf_lo(b); acc[4 * c + 3] = bf_hi(b);
      }
    }
    bar_sync(1, 128);
    fence_regs(acc);
#pragma unroll kGun2
    for (uint32_t u = 0; u < 28; u++) {
      WAIT_B(u & 3, (u >> 2) & 1);
      GEMM_CHUNK(G2DEPTH, wgmma_ss_n128_tb, acc, u < 7 ? dact + u * 512 : dxa + (u & 3) * 512, dbr + (u & 3) * 1024, false,
                 if (u > 0) REL_B(u - 1); if (u == 7) warp_arrive(bars + 8 * B_ACTOWN));
    }
    WG_WAIT(0);
    REL_B(3);
    if (tid == 128) PROF_MARK(5);
#pragma unroll 1
    for (uint32_t u = 0; u < 2; u++) {
      mbar_wait(bars + 8 * B_BFULL + 8 * u, 1);
      mbar_wait(bars + 8 * B_OOWN + 8 * u, 0);
      WG_FENCE();
#pragma unroll
      for (int kk = 0; kk < 4; kk++) wgmma_ss_n128_tb(acc, dxa + (4 + u) * 512 + kk * 2, dbr + u * 1024 + kk * 128, 1);
      WG_COMMIT(); WG_WAIT(0);
      REL_B(u);
    }
#pragma unroll 1
    for (uint32_t u = 0; u < 6; u++) {
      const uint32_t bs = u < 4 ? u + 2 : u - 4;
      mbar_wait(bars + 8 * B_BFULL + 8 * bs, u < 4 ? 1 : 0);
      mbar_wait(bars + 8 * B_OFULL + 8 * u, 0);
      const uint64_t db = (bs < 4 ? dbr : dbr - 8192) + bs * 1024;
      WG_FENCE();
#pragma unroll
      for (int kk = 0; kk < 4; kk++) wgmma_ss_n128_tb(acc, dact + u * 512 + kk * 2, db + kk * 128, 1);
      WG_COMMIT();
    }
    WG_WAIT(0);
    fence_regs(acc);
    if (tid == 128) PROF_MARK(6);
    {
      const uint32_t stg = sb + OFF_XA + 6 * 8192 + wq * 4096;
      const uint32_t r16 = st_row & 15;
#pragma unroll
      for (int c = 0; c < 16; c += 2) {
        const uint32_t unit = c + (lane >> 4);
        stsm_x4(stg + r16 * 256 + ((unit ^ (r16 & 7)) << 4), pack_bf16(acc[4 * c], acc[4 * c + 1]), pack_bf16(acc[4 * c + 2], acc[4 * c + 3]),
                pack_bf16(acc[4 * c + 4], acc[4 * c + 5]), pack_bf16(acc[4 * c + 6], acc[4 * c + 7]));
      }
      __syncwarp();
#pragma unroll
      for (int i = 0; i < 8; i++) {
        const uint32_t r = 2 * i + (lane >> 4), unit = lane & 15;
        uint4 v;
        asm volatile("ld.shared.v4.u32 {%0,%1,%2,%3}, [%4];" : "=r"(v.x), "=r"(v.y), "=r"(v.z), "=r"(v.w)
                     : "r"(stg + r * 256 + ((unit ^ (r & 7)) << 4)) : "memory");
        *reinterpret_cast<uint4*>(prm.out + (size_t)(rb * 64 + wq * 16 + r) * D_ + 128 * j + unit * 8) = v;
      }
    }
    if (tid == 128) PROF_MARK(7);
  } else {
    asm volatile("setmaxnreg.inc.sync.aligned.u32 %0;" ::"n"(REG_ATT));
    const int w = wg - 2;
    float sx[32], sy[32], o[4][12];
    uint32_t q[4][4], pa[16], pb[16];
#pragma unroll
    for (int i = 0; i < 32; i++) { sx[i] = 0.f; sy[i] = 0.f; }
    mbar_wait(bars + 8 * B_KVMMA, 0);
    fence_regs(sx);
    {
      const uint64_t da = desc_a(sb + OFF_XA), db = desc_b(sb + OFF_BR + w * 8192);
#pragma unroll 1
      for (int c = 0; c < 8; c++) {
        mbar_wait(bars + 8 * c, 0);
        WG_FENCE();
#pragma unroll
        for (int kk = 0; kk < 4; kk++) wgmma_ss_n64_tb(sx, da + c * 512 + kk * 2, db + c * 1024 + kk * 128, 1);
        WG_COMMIT();
        if (QTHR) WG_WAIT(0); else WG_WAIT(1);
        if (c > 0 && c <= 4) warp_arrive(bars + 8 * B_BEMPTY + 8 * (c - 1));
      }
    }
    WG_WAIT(0);
    fence_regs(sx);
    warp_arrive(bars + 8 * B_QDONE);
    float qmax = 0.f;
#pragma unroll
    for (int t = 0; t < 4; t++) {
      const float sc = 0.25f * 1.4426950408889634f;
      float n0 = 0.f, n1 = 0.f;
#pragma unroll
      for (int i = 0; i < 4; i++) {
        q[t][i] = pack_bf16(sx[8 * t + 2 * i] * sc, sx[8 * t + 2 * i + 1] * sc);
        const float n = bf_lo(q[t][i]) * bf_lo(q[t][i]) + bf_hi(q[t][i]) * bf_hi(q[t][i]);
        if (i & 1) n1 += n; else n0 += n;
      }
      n0 += __shfl_xor_sync(0xffffffffu, n0, 1); n1 += __shfl_xor_sync(0xffffffffu, n1, 1);
      n0 += __shfl_xor_sync(0xffffffffu, n0, 2); n1 += __shfl_xor_sync(0xffffffffu, n1, 2);
      asm("max.NaN.f32 %0, %1, %2;" : "=f"(n0) : "f"(n0), "f"(n1));
      asm("max.NaN.f32 %0, %1, %2;" : "=f"(qmax) : "f"(qmax), "f"(n0));
#pragma unroll
      for (int i = 0; i < 12; i++) o[t][i] = 0.f;
    }
    if (tid == 256) PROF_MARK(8);
    mbar_wait(bars + 8 * (B_KVFULL + 1), 0);
    uint32_t safe;
    {
      float kmax;
      asm volatile("ld.shared.f32 %0, [%1];" : "=f"(kmax) : "r"(sb + OFF_MISC + 32) : "memory");
      const uint32_t ok = (qmax * kmax <= 3600.f) ? 1u : 0u;
      asm volatile("{.reg .pred p, r; setp.ne.u32 p, %1, 0; bar.red.and.pred r, %2, 128, p; selp.u32 %0, 1, 0, r;}"
                   : "=r"(safe) : "r"(ok), "r"(2 + w) : "memory");
      safe = __shfl_sync(0xffffffffu, safe, 0);
    }
    if (tid == 256) PROF_MARK(9);
    const uint64_t dk0 = mkdesc(sb + OFF_KV, 2048, 128, 0), dv0 = mkdesc(sb + OFF_KV + 4096, 128, 2048, 0);
#pragma unroll
    for (int t = 0; t < 4; t++) { fence_regs(o[t]); fence_regs(q[t]); }
    fence_regs(sx); fence_regs(sy);
#define QK(S, T, DK) wgmma_rs_n64(S, q[T][0], q[T][1], q[T][2], q[T][3], DK, 0)
    if (safe) {
      uint32_t slot = 1, prev = 0, par = 0;
      for (int it = 0; it < 16; it++) {
        mbar_wait(bars + 8 * B_KVFULL + 8 * slot, par);
        const uint64_t dk = dk0 + slot * (KV_SLOT >> 4), dv = dv0 + slot * (KV_SLOT >> 4);
        WG_FENCE();
        QK(sx, 0, dk); WG_COMMIT();
        QK(sy, 1, dk); WG_COMMIT();
        WG_WAIT(1);
        if (it > 0) warp_arrive(bars + 8 * B_KVEMPTY + 8 * prev);
        constexpr int PD = SINGLEP ? 4 : 5;
        uint32_t (&p2)[16] = SINGLEP ? pa : pb;
#pragma unroll
        for (int s = 0; s < 8; s += 2) {
          if (s == 0) attn_step<PD, true, POLY_MASK>(sx, pa, o[0], dv);
          else attn_step<PD, false, POLY_MASK>(sx, pa, o[s & 3], dv + (s >> 2) * 64);
          if (s + 2 < 8) {
            QK(sx, (s + 2) & 3, dk + ((s + 2) >> 2) * 64); WG_COMMIT();
            attn_step<PD, false, POLY_MASK2>(sy, p2, o[(s + 1) & 3], dv + (s >> 2) * 64);
            QK(sy, (s + 3) & 3, dk + ((s + 3) >> 2) * 64); WG_COMMIT();
          } else {
            attn_step<PD - 1, false, POLY_MASK2>(sy, p2, o[(s + 1) & 3], dv + (s >> 2) * 64);
          }
        }
        prev = slot;
        if (++slot == 3) slot = 0;
        if (slot == 1) par ^= 1;
      }
      WG_WAIT(0);
    } else {
      float m[4][2];
#pragma unroll
      for (int t = 0; t < 4; t++) m[t][0] = m[t][1] = -INFINITY;
      uint32_t slot = 1, par = 0;
      for (int it = 0; it < 16; it++) {
        mbar_wait(bars + 8 * B_KVFULL + 8 * slot, par);
        for (int h = 0; h < 2; h++) {
          const uint64_t dk = dk0 + slot * (KV_SLOT >> 4) + h * 64, dv = dv0 + slot * (KV_SLOT >> 4) + h * 64;
#pragma unroll
          for (int t = 0; t < 4; t++) {
            WG_FENCE();
            QK(sx, t, dk); WG_COMMIT(); WG_WAIT(0);
            fence_regs(sx);
            float m0 = m[t][0], m1 = m[t][1];
#pragma unroll
            for (int i = 0; i < 8; i++) {
              m0 = fmaxf(m0, fmaxf(sx[4 * i], sx[4 * i + 1]));
              m1 = fmaxf(m1, fmaxf(sx[4 * i + 2], sx[4 * i + 3]));
            }
            m0 = fmaxf(m0, __shfl_xor_sync(0xffffffffu, m0, 1)); m1 = fmaxf(m1, __shfl_xor_sync(0xffffffffu, m1, 1));
            m0 = fmaxf(m0, __shfl_xor_sync(0xffffffffu, m0, 2)); m1 = fmaxf(m1, __shfl_xor_sync(0xffffffffu, m1, 2));
            const float a0 = ex2(m[t][0] - m0), a1 = ex2(m[t][1] - m1);
            m[t][0] = m0; m[t][1] = m1;
#pragma unroll
            for (int i = 0; i < 12; i++) o[t][i] *= (i & 2) ? a1 : a0;
#pragma unroll
            for (int i = 0; i < 16; i++) {
              const float mm = (i & 1) ? m1 : m0;
              pa[i] = pack_bf16(ex2(sx[2 * i] - mm), ex2(sx[2 * i + 1] - mm));
            }
            fence_regs(pa); fence_regs(o[t]);
            WG_FENCE();
#pragma unroll
            for (int c = 0; c < 4; c++) wgmma_rs_n24_tb(o[t], pa[4 * c], pa[4 * c + 1], pa[4 * c + 2], pa[4 * c + 3], dv + c * 16, 1);
            WG_COMMIT(); WG_WAIT(0);
            fence_regs(o[t]);
          }
        }
        warp_arrive(bars + 8 * B_KVEMPTY + 8 * slot);
        if (++slot == 3) slot = 0;
        if (slot == 1) par ^= 1;
      }
    }
#pragma unroll
    for (int t = 0; t < 4; t++) fence_regs(o[t]);
    if (tid == 256) PROF_MARK(10);
    if (tid == 384) PROF_MARK(11);
    mbar_wait(bars + 8 * (B_ACTT + 3), 0);
    const uint32_t st_row = wq * 16 + (lane & 7) + ((lane >> 3) & 1) * 8;
#pragma unroll
    for (int t = 0; t < 4; t++) {
      const float r0 = rcp(o[t][8]), r1 = rcp(o[t][10]);
      const uint32_t unit = 2 * t + (lane >> 4);
      stsm_x4(sb + OFF_XA + (4 + w) * 8192 + st_row * 128 + ((unit ^ (st_row & 7)) << 4),
              pack_bf16(o[t][0] * r0, o[t][1] * r0), pack_bf16(o[t][2] * r1, o[t][3] * r1),
              pack_bf16(o[t][4] * r0, o[t][5] * r0), pack_bf16(o[t][6] * r1, o[t][7] * r1));
    }
    fence_async_smem();
    __syncwarp();
    warp_arrive(bars + 8 * B_OOWN + 8 * w);
    bar_sync(2 + w, 128);
    if (wq == 0) {
      warp_bulk_store(g_s.ex + (blockIdx.x * 9 + 7 + w) * 512, sb + OFF_XA + (4 + w) * 8192, 8192);
      if (tid == 256) PROF_MARK(22);
      warp_publish(g_oflag + (blockIdx.x * 2 + w) * 8, get_epoch(), 0);
      if (tid == 256) PROF_MARK(23);
    }
  }
}

typedef CUresult (*EncodeFn)(CUtensorMap*, CUtensorMapDataType, cuuint32_t, void*, const cuuint64_t*, const cuuint64_t*,
                             const cuuint32_t*, const cuuint32_t*, CUtensorMapInterleave, CUtensorMapSwizzle,
                             CUtensorMapL2promotion, CUtensorMapFloatOOBfill);

void make_map(EncodeFn fn, CUtensorMap* m, const void* p, uint64_t rows, uint64_t cols, uint32_t box_rows, uint32_t box_groups) {
  const cuuint64_t dims[3] = {64, rows, cols / 64};
  const cuuint64_t strides[2] = {cols * 2, 128};
  const cuuint32_t box[3] = {64, box_rows, box_groups}, es[3] = {1, 1, 1};
  fn(m, CU_TENSOR_MAP_DATA_TYPE_BFLOAT16, 3, const_cast<void*>(p), dims, strides, box, es, CU_TENSOR_MAP_INTERLEAVE_NONE,
     CU_TENSOR_MAP_SWIZZLE_128B, CU_TENSOR_MAP_L2_PROMOTION_L2_128B, CU_TENSOR_MAP_FLOAT_OOB_FILL_NONE);
}

}

extern "C" void kernel_launch(void* const* d_in, const int* in_sizes, int n_in, void* d_out, int out_size) {
  (void)in_sizes; (void)n_in; (void)out_size;
  void* fnp = nullptr;
  cudaDriverEntryPointQueryResult qr;
  cudaGetDriverEntryPoint("cuTensorMapEncodeTiled", &fnp, cudaEnableDefault, &qr);
  EncodeFn fn = reinterpret_cast<EncodeFn>(fnp);
  CUtensorMap mq, m1, m1t, m2, mo;
  make_map(fn, &mq, d_in[1], D_, D_, 64, 2);
  make_map(fn, &m1, d_in[6], D_, F_, 64, 2);
  make_map(fn, &m1t, d_in[6], D_, F_, 128, 1);
  make_map(fn, &m2, d_in[8], F_, D_, 64, 2);
  make_map(fn, &mo, d_in[4], D_, D_, 64, 2);
  Params p;
  p.x = (const __nv_bfloat16*)d_in[0]; p.wq = (const __nv_bfloat16*)d_in[1]; p.wk = (const __nv_bfloat16*)d_in[2]; p.wv = (const __nv_bfloat16*)d_in[3];
  p.b1 = (const __nv_bfloat16*)d_in[7]; p.w1 = (const __nv_bfloat16*)d_in[6]; p.w2 = (const __nv_bfloat16*)d_in[8];
  p.wo = (const __nv_bfloat16*)d_in[4]; p.out = (__nv_bfloat16*)d_out;
  cudaFuncSetAttribute(fused_kernel, cudaFuncAttributeMaxDynamicSharedMemorySize, SMEM_BYTES);
  fused_kernel<<<NCTA, 512, SMEM_BYTES>>>(mq, m1, m1t, m2, mo, p);
}
```

```cpp
#include <cuda_runtime.h>
#include <cuda_bf16.h>
#include <cuda.h>
#include <stdint.h>

namespace {

constexpr int D_ = 512, F_ = 1792;
constexpr int NCTA = 128;

#define G1DEPTH 2
#define G2DEPTH 1
#define USE_HELP 1
#define SKEW 8
#define POLY_MASK 0x6D75u
constexpr int REG_ATT = 192, REG_GEMM = 104, REG_PROD = 24;
static_assert(2 * REG_ATT + REG_GEMM + REG_PROD <= 512, "register pool");

constexpr uint32_t OFF_XA  = 0;
constexpr uint32_t OFF_BR  = 65536;
constexpr uint32_t OFF_ACT = OFF_BR + 65536;
constexpr uint32_t OFF_KV  = OFF_ACT + 57344;
constexpr uint32_t OFF_WKV = OFF_KV + 30720;
constexpr uint32_t OFF_B1  = OFF_WKV + 8192;
constexpr uint32_t OFF_KVO = OFF_B1 + 1792;
constexpr uint32_t OFF_RATIO = OFF_KVO + 1024;
constexpr uint32_t OFF_BAR = OFF_RATIO + 256;
constexpr uint32_t SMEM_BYTES = OFF_BAR + 640 + 1024;
static_assert(SMEM_BYTES <= 232448, "smem");
constexpr uint32_t KV_SLOT = 10240;

enum : uint32_t {
  B_BFULL = 0, B_QFULL = 4, B_HFULL = 8  , B_KVFULL = 12, B_OFULL = 15,
  B_BEMPTY = 21, B_KVEMPTY = 25, B_QDONE = 28,
  B_OOWN = 33, B_LAST = 35, B_ACTOWN = 36, B_ACTT = 37, B_XNSENT = 41, B_KVMMA = 42, B_SKEW = 43, B_EPOCH = 44, B_COUNT = 45
};
constexpr uint32_t OFF_MISC = OFF_BAR + 8 * 46;

struct __align__(1024) Scratch {
  uint4    kv[16 * 512];
  uint2    kvflag[NCTA * 4];
  uint32_t oflag[NCTA * 2 * 8];
  uint32_t actflag[NCTA * 8];
  uint32_t xnflag[NCTA * 8];
  uint32_t hflag[64 * 8];
  __align__(32) uint32_t epoch;
  uint32_t pad[255];
  uint4    ratio[32 * 16];
  uint4    xn[32 * 8 * 512];
  uint4    ex[NCTA * 9 * 512];
};
__device__ Scratch g_s;
#define g_kv g_s.kv
#define g_kvflag g_s.kvflag
#define g_oflag g_s.oflag
#define g_actflag g_s.actflag
#define g_epoch g_s.epoch
#define PROF_MARK(i) do {} while (0)

#define WG_FENCE()  asm volatile("wgmma.fence.sync.aligned;" ::: "memory")
#define WG_COMMIT() asm volatile("wgmma.commit_group.sync.aligned;" ::: "memory")
#define WG_WAIT(n)  asm volatile("wgmma.wait_group.sync.aligned %0;" ::"n"(n) : "memory")

__device__ __forceinline__ void wgmma_ss_n8_tb(float (&d)[4], uint64_t da, uint64_t db, int sd) {
  asm volatile("{.reg .pred p; setp.ne.b32 p, %6, 0;\n"
      "wgmma.mma_async.sync.aligned.m64n8k16.f32.bf16.bf16 {"
      "%0, %1, %2, %3"
      "}, %4, %5, p, 1, 1, 0, 1;}\n"
      : "+f"(d[0]), "+f"(d[1]), "+f"(d[2]), "+f"(d[3])
      : "l"(da), "l"(db), "r"(sd));
}
__device__ __forceinline__ void wgmma_ss_n64_tb(float (&d)[32], uint64_t da, uint64_t db, int sd) {
  asm volatile("{.reg .pred p; setp.ne.b32 p, %34, 0;\n"
      "wgmma.mma_async.sync.aligned.m64n64k16.f32.bf16.bf16 {"
      "%0, %1, %2, %3, %4, %5, %6, %7, %8, %9, %10, %11, %12, %13, %14, %15,"
      "%16, %17, %18, %19, %20, %21, %22, %23, %24, %25, %26, %27, %28, %29, %30, %31"
      "}, %32, %33, p, 1, 1, 0, 1;}\n"
      : "+f"(d[0]), "+f"(d[1]), "+f"(d[2]), "+f"(d[3]), "+f"(d[4]), "+f"(d[5]), "+f"(d[6]), "+f"(d[7]),
        "+f"(d[8]), "+f"(d[9]), "+f"(d[10]), "+f"(d[11]), "+f"(d[12]), "+f"(d[13]), "+f"(d[14]), "+f"(d[15]),
        "+f"(d[16]), "+f"(d[17]), "+f"(d[18]), "+f"(d[19]), "+f"(d[20]), "+f"(d[21]), "+f"(d[22]), "+f"(d[23]),
        "+f"(d[24]), "+f"(d[25]), "+f"(d[26]), "+f"(d[27]), "+f"(d[28]), "+f"(d[29]), "+f"(d[30]), "+f"(d[31])
      : "l"(da), "l"(db), "r"(sd));
}
__device__ __forceinline__ void wgmma_ss_n128_tb(float (&d)[64], uint64_t da, uint64_t db, int sd) {
  asm volatile("{.reg .pred p; setp.ne.b32 p, %66, 0;\n"
      "wgmma.mma_async.sync.aligned.m64n128k16.f32.bf16.bf16 {"
      "%0, %1, %2, %3, %4, %5, %6, %7, %8, %9, %10, %11, %12, %13, %14, %15,"
      "%16, %17, %18, %19, %20, %21, %22, %23, %24, %25, %26, %27, %28, %29, %30, %31,"
      "%32, %33, %34, %35, %36, %37, %38, %39, %40, %41, %42, %43, %44, %45, %46, %47,"
      "%48, %49, %50, %51, %52, %53, %54, %55, %56, %57, %58, %59, %60, %61, %62, %63"
      "}, %64, %65, p, 1, 1, 0, 1;}\n"
      : "+f"(d[0]), "+f"(d[1]), "+f"(d[2]), "+f"(d[3]), "+f"(d[4]), "+f"(d[5]), "+f"(d[6]), "+f"(d[7]),
        "+f"(d[8]), "+f"(d[9]), "+f"(d[10]), "+f"(d[11]), "+f"(d[12]), "+f"(d[13]), "+f"(d[14]), "+f"(d[15]),
        "+f"(d[16]), "+f"(d[17]), "+f"(d[18]), "+f"(d[19]), "+f"(d[20]), "+f"(d[21]), "+f"(d[22]), "+f"(d[23]),
        "+f"(d[24]), "+f"(d[25]), "+f"(d[26]), "+f"(d[27]), "+f"(d[28]), "+f"(d[29]), "+f"(d[30]), "+f"(d[31]),
        "+f"(d[32]), "+f"(d[33]), "+f"(d[34]), "+f"(d[35]), "+f"(d[36]), "+f"(d[37]), "+f"(d[38]), "+f"(d[39]),
        "+f"(d[40]), "+f"(d[41]), "+f"(d[42]), "+f"(d[43]), "+f"(d[44]), "+f"(d[45]), "+f"(d[46]), "+f"(d[47]),
        "+f"(d[48]), "+f"(d[49]), "+f"(d[50]), "+f"(d[51]), "+f"(d[52]), "+f"(d[53]), "+f"(d[54]), "+f"(d[55]),
        "+f"(d[56]), "+f"(d[57]), "+f"(d[58]), "+f"(d[59]), "+f"(d[60]), "+f"(d[61]), "+f"(d[62]), "+f"(d[63])
      : "l"(da), "l"(db), "r"(sd));
}
__device__ __forceinline__ void wgmma_rs_n64(float (&d)[32], uint32_t a0, uint32_t a1, uint32_t a2, uint32_t a3, uint64_t db, int sd) {
  asm volatile("{.reg .pred p; setp.ne.b32 p, %37, 0;\n"
      "wgmma.mma_async.sync.aligned.m64n64k16.f32.bf16.bf16 {"
      "%0, %1, %2, %3, %4, %5, %6, %7, %8, %9, %10, %11, %12, %13, %14, %15,"
      "%16, %17, %18, %19, %20, %21, %22, %23, %24, %25, %26, %27, %28, %29, %30, %31"
      "}, {%32,%33,%34,%35}, %36, p, 1, 1, 0;}\n"
      : "+f"(d[0]), "+f"(d[1]), "+f"(d[2]), "+f"(d[3]), "+f"(d[4]), "+f"(d[5]), "+f"(d[6]), "+f"(d[7]),
        "+f"(d[8]), "+f"(d[9]), "+f"(d[10]), "+f"(d[11]), "+f"(d[12]), "+f"(d[13]), "+f"(d[14]), "+f"(d[15]),
        "+f"(d[16]), "+f"(d[17]), "+f"(d[18]), "+f"(d[19]), "+f"(d[20]), "+f"(d[21]), "+f"(d[22]), "+f"(d[23]),
        "+f"(d[24]), "+f"(d[25]), "+f"(d[26]), "+f"(d[27]), "+f"(d[28]), "+f"(d[29]), "+f"(d[30]), "+f"(d[31])
      : "r"(a0), "r"(a1), "r"(a2), "r"(a3), "l"(db), "r"(sd));
}
__device__ __forceinline__ void wgmma_rs_n24_tb(float (&d)[12], uint32_t a0, uint32_t a1, uint32_t a2, uint32_t a3, uint64_t db, int sd) {
  asm volatile("{.reg .pred p; setp.ne.b32 p, %17, 0;\n"
      "wgmma.mma_async.sync.aligned.m64n24k16.f32.bf16.bf16 {"
      "%0, %1, %2, %3, %4, %5, %6, %7, %8, %9, %10, %11"
      "}, {%12,%13,%14,%15}, %16, p, 1, 1, 1;}\n"
      : "+f"(d[0]), "+f"(d[1]), "+f"(d[2]), "+f"(d[3]), "+f"(d[4]), "+f"(d[5]), "+f"(d[6]), "+f"(d[7]),
        "+f"(d[8]), "+f"(d[9]), "+f"(d[10]), "+f"(d[11])
      : "r"(a0), "r"(a1), "r"(a2), "r"(a3), "l"(db), "r"(sd));
}

template <int N> __device__ __forceinline__ void fence_regs(float (&a)[N]) {
#pragma unroll
  for (int i = 0; i < N; i++) asm volatile("" : "+f"(a[i])::"memory");
}
template <int N> __device__ __forceinline__ void fence_regs(uint32_t (&a)[N]) {
#pragma unroll
  for (int i = 0; i < N; i++) asm volatile("" : "+r"(a[i])::"memory");
}
__host__ __device__ constexpr uint64_t mkdesc(uint32_t addr, uint32_t lbo, uint32_t sbo, uint32_t swz) {
  return (uint64_t)((addr & 0x3FFFF) >> 4) | ((uint64_t)(lbo >> 4) << 16) | ((uint64_t)(sbo >> 4) << 32) | ((uint64_t)swz << 62);
}
__host__ __device__ constexpr uint64_t desc_a(uint32_t addr) { return mkdesc(addr, 16, 1024, 1); }
__host__ __device__ constexpr uint64_t desc_b(uint32_t addr) { return mkdesc(addr, 8192, 1024, 1); }

__device__ __forceinline__ void mbar_init(uint32_t bar, uint32_t cnt) {
  asm volatile("mbarrier.init.shared::cta.b64 [%0], %1;" ::"r"(bar), "r"(cnt) : "memory");
}
__device__ __forceinline__ void warp_arrive(uint32_t bar, uint32_t n = 1) {
  asm volatile("{.reg .pred p; elect.sync _|p, 0xffffffff; @p mbarrier.arrive.shared::cta.b64 _, [%0], %1;}" ::"r"(bar), "r"(n) : "memory");
}
__device__ __forceinline__ void mbar_expect(uint32_t bar, uint32_t bytes) {
  asm volatile("mbarrier.arrive.expect_tx.shared::cta.b64 _, [%0], %1;" ::"r"(bar), "r"(bytes) : "memory");
}
__device__ __forceinline__ void mbar_wait(uint32_t bar, uint32_t parity) {
  asm volatile(
      "{.reg .pred p; .reg .u32 c;\n"
      "mbarrier.try_wait.parity.shared::cta.b64 p, [%0], %1;\n"
      "@p bra DONE;\n"
      "mov.u32 c, 0;\n"
      "LOOP:\n"
      "mbarrier.try_wait.parity.shared::cta.b64 p, [%0], %1;\n"
      "@p bra DONE;\n"
      "add.u32 c, c, 1;\n"
      "setp.lt.u32 p, c, 4000000;\n"
      "@p bra LOOP;\n"
      "trap;\n"
      "DONE:\n"
      "}\n" ::"r"(bar), "r"(parity) : "memory");
}
__device__ __forceinline__ void warp_tma(uint32_t dst, const CUtensorMap* map, int row, int grp, uint32_t bar) {
  asm volatile("{.reg .pred p; elect.sync _|p, 0xffffffff;\n"
               "@p mbarrier.arrive.expect_tx.shared::cta.b64 _, [%2], 16384;\n"
               "@p cp.async.bulk.tensor.3d.shared::cluster.global.mbarrier::complete_tx::bytes [%0], [%1, {%5, %3, %4}], [%2];}"
               ::"r"(dst), "l"(map), "r"(bar), "r"(row), "r"(grp), "r"(0) : "memory");
}
__device__ __forceinline__ void warp_tma_ab(uint32_t dst, const CUtensorMap* map, int row, int grp, uint32_t bar, uint32_t dsta, const void* srca) {
  asm volatile("{.reg .pred p; elect.sync _|p, 0xffffffff;\n"
               "@p mbarrier.arrive.expect_tx.shared::cta.b64 _, [%2], 24576;\n"
               "@p cp.async.bulk.shared::cluster.global.mbarrier::complete_tx::bytes [%6], [%7], 8192, [%2];\n"
               "@p cp.async.bulk.tensor.3d.shared::cluster.global.mbarrier::complete_tx::bytes [%0], [%1, {%5, %3, %4}], [%2];}"
               ::"r"(dst), "l"(map), "r"(bar), "r"(row), "r"(grp), "r"(0), "r"(dsta), "l"(srca) : "memory");
}
__device__ __forceinline__ void warp_bulk_load(uint32_t dst, const void* src, uint32_t bar) {
  asm volatile("{.reg .pred p; elect.sync _|p, 0xffffffff;\n"
               "@p mbarrier.arrive.expect_tx.shared::cta.b64 _, [%2], 8192;\n"
               "@p cp.async.bulk.shared::cluster.global.mbarrier::complete_tx::bytes [%0], [%1], 8192, [%2];}"
               ::"r"(dst), "l"(src), "r"(bar) : "memory");
}
__device__ __forceinline__ void warp_bulk_store(void* dst, uint32_t src, uint32_t bytes) {
  asm volatile("{.reg .pred p; elect.sync _|p, 0xffffffff;\n"
               "@p cp.async.bulk.global.shared::cta.bulk_group [%0], [%1], %2;\n"
               "@p cp.async.bulk.commit_group;}" ::"l"(dst), "r"(src), "r"(bytes) : "memory");
}
__device__ __forceinline__ void warp_publish(void* flag, uint32_t v0, uint32_t v1) {
  asm volatile("{.reg .pred p; elect.sync _|p, 0xffffffff;\n"
               "cp.async.bulk.wait_group 0;\n"
               "@p st.relaxed.gpu.global.v2.u32 [%0], {%1,%2};}" ::"l"(flag), "r"(v0), "r"(v1) : "memory");
}
__device__ __forceinline__ void bulk_load(uint32_t dst, const void* src, uint32_t bytes, uint32_t bar) {
  asm volatile("cp.async.bulk.shared::cluster.global.mbarrier::complete_tx::bytes [%0], [%1], %2, [%3];"
               ::"r"(dst), "l"(src), "r"(bytes), "r"(bar) : "memory");
}
__device__ __forceinline__ void l2_prefetch(const void* p, uint32_t bytes) {
  asm volatile("cp.async.bulk.prefetch.L2.global [%0], %1;" ::"l"(p), "r"(bytes) : "memory");
}
__device__ __forceinline__ void fence_async_smem() { asm volatile("fence.proxy.async.shared::cta;" ::: "memory"); }
__device__ __forceinline__ void fence_async_gmem() { asm volatile("fence.proxy.async.global;" ::: "memory"); }
__device__ __forceinline__ void bar_sync(int id, int n) { asm volatile("bar.sync %0, %1;" ::"r"(id), "r"(n) : "memory"); }
__device__ __forceinline__ void st_flag(uint32_t* p, uint32_t v) {
  asm volatile("st.relaxed.gpu.global.u32 [%0], %1;" ::"l"(p), "r"(v) : "memory");
}
__device__ __forceinline__ uint32_t ld_flag(const uint32_t* p) {
  uint32_t v;
  asm volatile("ld.relaxed.gpu.global.u32 %0, [%1];" : "=r"(v) : "l"(p) : "memory");
  return v;
}
__device__ __forceinline__ void poll_flag(const uint32_t* p, uint32_t want) {
  uint32_t n = 0;
  while (ld_flag(p) != want)
    if (++n > 4000000u) __trap();
}
__device__ __forceinline__ void stsm_x4(uint32_t addr, uint32_t r0, uint32_t r1, uint32_t r2, uint32_t r3) {
  asm volatile("stmatrix.sync.aligned.m8n8.x4.shared.b16 [%0], {%1,%2,%3,%4};" ::"r"(addr), "r"(r0), "r"(r1), "r"(r2), "r"(r3) : "memory");
}
__device__ __forceinline__ void sts128(uint32_t addr, uint32_t r0, uint32_t r1, uint32_t r2, uint32_t r3) {
  asm volatile("st.shared.v4.u32 [%0], {%1,%2,%3,%4};" ::"r"(addr), "r"(r0), "r"(r1), "r"(r2), "r"(r3) : "memory");
}
__device__ __forceinline__ int fresh_tid() { int v; asm volatile("mov.u32 %0, %%tid.x;" : "=r"(v)); return v; }
__device__ __forceinline__ float ex2(float x) { float y; asm("ex2.approx.ftz.f32 %0, %1;" : "=f"(y) : "f"(x)); return y; }
__device__ __forceinline__ float rcp(float x) { float y; asm("rcp.approx.ftz.f32 %0, %1;" : "=f"(y) : "f"(x)); return y; }
__device__ __forceinline__ uint32_t pack_bf16(float lo, float hi) {
  uint32_t y; asm("cvt.rn.bf16x2.f32 %0, %1, %2;" : "=r"(y) : "f"(hi), "f"(lo)); return y;
}
__device__ __forceinline__ float bf_lo(uint32_t v) { return __uint_as_float(v << 16); }
__device__ __forceinline__ float bf_hi(uint32_t v) { return __uint_as_float(v & 0xFFFF0000u); }
__device__ __forceinline__ uint32_t hfma2bf(uint32_t a, uint32_t b, uint32_t c) {
  uint32_t d; asm("fma.rn.bf16x2 %0, %1, %2, %3;" : "=r"(d) : "r"(a), "r"(b), "r"(c)); return d;
}
__device__ __forceinline__ uint32_t exp2_pair_fma(float a, float b) {
  const float M = 98304.f + 127.f;
  uint32_t x = __byte_perm(__float_as_uint(a + M), __float_as_uint(b + M), 0x5410);
  uint32_t y, r;
  asm("lop3.b32 %0, %1, 0x007F007F, %2, 0xEA;" : "=r"(y) : "r"(x), "r"(0x3F803F80u));
  const uint32_t h = hfma2bf(y, hfma2bf(y, 0x3EAF3EAFu, 0xBD09BD09u), 0x3F323F32u);
  asm("lop3.b32 %0, %1, 0x007F007F, %2, 0xB8;" : "=r"(r) : "r"(x), "r"(h));
  return r;
}

template <int PEND>
__device__ __forceinline__ void attn_step(float (&s)[32], uint32_t (&p)[16], float (&o)[12], uint64_t dv) {
  if (PEND >= 0) WG_WAIT(PEND < 0 ? 0 : PEND);
  fence_regs(s);
#pragma unroll
  for (int c = 0; c < 4; c++) {
#pragma unroll
    for (int i = 4 * c; i < 4 * c + 4; i++)
      p[i] = ((POLY_MASK >> i) & 1) ? exp2_pair_fma(s[2 * i], s[2 * i + 1]) : pack_bf16(ex2(s[2 * i]), ex2(s[2 * i + 1]));
#pragma unroll
    for (int i = 4 * c; i < 4 * c + 4; i++) asm volatile("" : "+r"(p[i])::"memory");
    WG_FENCE();
    wgmma_rs_n24_tb(o, p[4 * c], p[4 * c + 1], p[4 * c + 2], p[4 * c + 3], dv + c * 16, 1);
    WG_COMMIT();
  }
}

template <int NC>
__device__ __forceinline__ void mish_store(const float (&acc)[64], float ratio0, float ratio1, uint32_t b1a, uint32_t sta, uint32_t stx,
                                           const uint32_t* breg = nullptr) {
#pragma unroll
  for (int c = 0; c < NC; c += 2) {
    uint32_t r[4];
#pragma unroll
    for (int u = 0; u < 2; u++) {
      float b0, b1, a[4];
      if (breg) { b0 = bf_lo(breg[c + u]); b1 = bf_hi(breg[c + u]); }
      else asm volatile("ld.shared.v2.f32 {%0,%1}, [%2];" : "=f"(b0), "=f"(b1) : "r"(b1a + (c + u) * 32));
#pragma unroll
      for (int e = 0; e < 4; e++) {
        const float h = fmaf(acc[4 * (c + u) + e], (e & 2) ? ratio1 : ratio0, (e & 1) ? b1 : b0);
        const float w = fmaf(ex2(h * 1.4426950408889634f), 0.7071067811865476f, 0.7071067811865476f);
        a[e] = fmaf(-h, rcp(fmaf(w, w, 0.5f)), h);
      }
      r[2 * u] = pack_bf16(a[0], a[1]); r[2 * u + 1] = pack_bf16(a[2], a[3]);
    }
    stsm_x4(sta + (c >> 3) * 8192 + (stx ^ ((c & 7) << 4)), r[0], r[1], r[2], r[3]);
  }
}

struct Params {
  const __nv_bfloat16 *x, *wq, *wk, *wv, *b1, *w1, *w2, *wo;
  __nv_bfloat16* out;
};

#define GEMM_CHUNK(GDEPTH, WGMMA, ACC, DA, DB, FIRST, REL_PREV)                              \
  do {                                                                                       \
    const uint64_t da_ = (DA), db_ = (DB);                                                   \
    WG_FENCE();                                                                              \
    _Pragma("unroll") for (int kk = 0; kk < 4; kk++) {                                       \
      WGMMA(ACC, da_ + kk * 2, db_ + kk * 128, !((FIRST) && kk == 0));                       \
      if (GDEPTH == 1) { WG_COMMIT(); WG_WAIT(0); if (kk == 0) { REL_PREV; } }               \
      if (GDEPTH == 2) { WG_COMMIT(); WG_WAIT(1); if (kk == 0) { REL_PREV; } }               \
    }                                                                                        \
    if (GDEPTH == 4) { WG_COMMIT(); WG_WAIT(1); REL_PREV; }                                  \
  } while (0)

template <bool HELP>
__global__ void __launch_bounds__(512, 1)
fused_kernel(const Params prm, const __grid_constant__ CUtensorMap map_wq, const __grid_constant__ CUtensorMap map_w1,
             const __grid_constant__ CUtensorMap map_w1t, const __grid_constant__ CUtensorMap map_w2,
             const __grid_constant__ CUtensorMap map_wo) {
  extern __shared__ uint8_t smem_raw[];
  constexpr uint32_t sb = 1024, bars = sb + OFF_BAR;
  const int tid = threadIdx.x, lane = tid & 31, warp = __shfl_sync(0xffffffffu, tid >> 5, 0);
  const int rb = blockIdx.x >> 2, j = blockIdx.x & 3;

  auto init_barriers = [&]() {
#pragma unroll
    for (uint32_t i = 0; i < B_COUNT; i++) mbar_init(bars + 8 * i, i < B_BEMPTY || i == B_EPOCH ? 1 : i <= B_QDONE ? 8 : 4);
    asm volatile("fence.mbarrier_init.release.cluster;" ::: "memory");
    mbar_expect(bars + 8 * B_EPOCH, 16);
    bulk_load(sb + OFF_MISC, &g_epoch, 16, bars + 8 * B_EPOCH);
  };
  auto get_epoch = [&]() {
    uint32_t e;
    mbar_wait(bars + 8 * B_EPOCH, 0);
    asm volatile("ld.shared.u32 %0, [%1];" : "=r"(e) : "r"(sb + OFF_MISC) : "memory");
    return e + 1;
  };
  constexpr int NOWN = HELP ? 6 : 7;
  constexpr uint32_t PH = HELP ? 1 : 0;

  if (HELP && blockIdx.x >= NCTA) {
    const int jp = blockIdx.x & 1, rb0 = ((blockIdx.x >> 1) & 1) * 16, hw = warp >> 2, wq = warp & 3;
    constexpr uint32_t OFF_HST = OFF_KV + 8192, OFF_HRA = OFF_HST + 32768;
    static_assert(OFF_HRA + 512 <= OFF_BAR, "helper smem");
    if (tid == 0) init_barriers();
    __syncthreads();
    if (hw < 2) {
    asm volatile("setmaxnreg.dec.sync.aligned.u32 40;");
    const uint32_t epoch = get_epoch();
    if (warp == 0) {
#pragma unroll 1
      for (int c = 0; c < 8; c++) warp_tma(sb + OFF_BR + c * 16384, &map_w1t, 128 * (c & 3), 7 * (2 * jp + (c >> 2)) + 6, bars + 8 * c);
      poll_flag(g_s.xnflag + (rb0 * 4 + lane) * 8, epoch);
      poll_flag(g_s.xnflag + (rb0 * 4 + 32 + lane) * 8, epoch);
      fence_async_gmem();
      __syncwarp();
#pragma unroll 1
      for (int b = 0; b < 16; b++) {
#pragma unroll 1
        for (int p = 0; p < 4; p++) {
          if (b > 0) mbar_wait(bars + 8 * B_ACTT + 8 * p, (b - 1) & 1);
          asm volatile("{.reg .pred p; elect.sync _|p, 0xffffffff;\n"
                       "@p mbarrier.arrive.expect_tx.shared::cta.b64 _, [%2], 16448;\n"
                       "@p cp.async.bulk.shared::cluster.global.mbarrier::complete_tx::bytes [%0], [%1], 16384, [%2];\n"
                       "@p cp.async.bulk.shared::cluster.global.mbarrier::complete_tx::bytes [%3], [%4], 64, [%2];}"
                       ::"r"(sb + OFF_XA + p * 16384), "l"(g_s.xn + ((rb0 + b) * 8 + 2 * p) * 512), "r"(bars + 8 * B_HFULL + 8 * p + 32 * (b & 1)),
                         "r"(sb + OFF_HRA + (b & 1) * 256 + p * 64), "l"(g_s.ratio + (rb0 + b) * 16 + p * 4) : "memory");
        }
      }
    } else if (warp < 3) {
      const int w = warp - 1;
#pragma unroll 1
      for (int b = w; b < 16; b += 2) {
        mbar_wait(bars + 8 * B_OOWN + 8 * w, (b >> 1) & 1);
        warp_bulk_store(g_s.ex + (((rb0 + b) * 4 + 2 * jp) * 9 + 6) * 512, sb + OFF_HST + w * 16384, 8192);
        warp_bulk_store(g_s.ex + (((rb0 + b) * 4 + 2 * jp + 1) * 9 + 6) * 512, sb + OFF_HST + w * 16384 + 8192, 8192);
        warp_publish(g_s.hflag + ((rb0 + b) * 2 + jp) * 8, epoch, 0);
        warp_arrive(bars + 8 * B_LAST + 8 * w, 4);
      }
    }
    } else {
      asm volatile("setmaxnreg.inc.sync.aligned.u32 208;");
      const int w = hw & 1, g = lane >> 2;
      const uint32_t st_row = wq * 16 + (lane & 7) + ((lane >> 3) & 1) * 8;
      constexpr uint64_t da = desc_a(sb + OFF_XA), db = mkdesc(sb + OFF_BR, 65536, 1024, 1);
      float acc[64];
      uint32_t breg[16];
#pragma unroll
      for (int i = 0; i < 64; i++) acc[i] = 0.f;
#pragma unroll
      for (int c = 0; c < 16; c++)
        breg[c] = __ldg(reinterpret_cast<const uint32_t*>(prm.b1 + 448 * (2 * jp + (c >> 3)) + 384 + (c & 7) * 8) + (lane & 3));
#pragma unroll 1
      for (int c = 0; c < 8; c++) mbar_wait(bars + 8 * c, 0);
#pragma unroll 1
      for (int b = w; b < 16; b += 2) {
        fence_regs(acc);
        float ratio0 = 0.f, ratio1 = 0.f;
#pragma unroll
        for (int p = 0; p < 4; p++) {
          mbar_wait(bars + 8 * (B_HFULL + p) + 32 * w, (b >> 1) & 1);
          if (p == wq) {
            asm volatile("ld.shared.f32 %0, [%1];" : "=f"(ratio0) : "r"(sb + OFF_HRA + w * 256 + (wq * 16 + g) * 4) : "memory");
            asm volatile("ld.shared.f32 %0, [%1];" : "=f"(ratio1) : "r"(sb + OFF_HRA + w * 256 + (wq * 16 + g + 8) * 4) : "memory");
          }
          WG_FENCE();
#pragma unroll
          for (int kk = 0; kk < 8; kk++)
            wgmma_ss_n128_tb(acc, da + p * 1024 + (kk >> 2) * 512 + (kk & 3) * 2, db + p * 1024 + kk * 128, p + kk > 0);
          WG_COMMIT(); WG_WAIT(1);
          if (p > 0) warp_arrive(bars + 8 * B_ACTT + 8 * (p - 1));
        }
        WG_WAIT(0);
        fence_regs(acc);
        warp_arrive(bars + 8 * B_ACTT + 24);
        mbar_wait(bars + 8 * B_LAST + 8 * w, ((b >> 1) & 1) ^ 1);
        mish_store<16>(acc, ratio0, ratio1, 0, sb + OFF_HST + w * 16384 + st_row * 128, ((lane >> 4) ^ (st_row & 7)) << 4, breg);
        fence_async_smem();
        __syncwarp();
        warp_arrive(bars + 8 * B_OOWN + 8 * w);
      }
    }
    return;
  }

  if (warp == 0) {
    if ((uint32_t)__cvta_generic_to_shared(smem_raw) > sb) __trap();
    if (lane == 0) {
      l2_prefetch(reinterpret_cast<const uint8_t*>(prm.wq) + blockIdx.x * 4096, 4096);
      init_barriers();
    }
    __syncwarp();
    asm volatile("bar.arrive 0, 512;" ::: "memory");
    bar_sync(4, 512);
    if (lane == 0) PROF_MARK(13);
#pragma unroll 1
    for (int c = 0; c < 8; c++) warp_tma(sb + OFF_BR + c * 16384, &map_wq, 64 * c, 2 * j, bars + 8 * c);
  } else {
    const int row4 = warp * 4, row5 = warp == 13 ? 3 : (warp >> 2) - 1;
    uint4 v[5][2];
    const uint4* xr = reinterpret_cast<const uint4*>(prm.x + (size_t)(rb * 64) * D_) + lane;
    const bool five = (warp & 3) == 0 || warp == 13;
#pragma unroll
    for (int r = 0; r < 4; r++) { v[r][0] = __ldg(xr + (row4 + r) * 64); v[r][1] = __ldg(xr + (row4 + r) * 64 + 32); }
    v[4][0] = v[4][1] = make_uint4(0, 0, 0, 0);
    if (five) { v[4][0] = __ldg(xr + row5 * 64); v[4][1] = __ldg(xr + row5 * 64 + 32); }
    if (tid == 160) PROF_MARK(26);
    const __nv_bfloat16* wsrc = (j < 2 ? prm.wk : prm.wv) + (j & 1) * 8;
    const uint4 wkv = __ldg(reinterpret_cast<const uint4*>(wsrc + tid * 16));
    uint4 wkv0 = make_uint4(0, 0, 0, 0);
    if (warp == 15) wkv0 = __ldg(reinterpret_cast<const uint4*>(wsrc + lane * 16));
    float b1v = 0.f;
    if (tid >= 64) b1v = __bfloat162float(prm.b1[448 * j + tid - 64]);
    if (tid >= 128) {
      const int t = tid - 128;
      sts128(sb + OFF_KV + (t >> 7) * KV_SLOT + 8192 + (t & 127) * 16, 0x3F803F80u, 0x3F803F80u, 0x3F803F80u, 0x3F803F80u);
    }
    float mu[5], rs[5];
#pragma unroll
    for (int r = 0; r < 5; r++) {
      mu[r] = rs[r] = 0.f;
      if (r < 4 || five) {
        const uint32_t w[8] = {v[r][0].x, v[r][0].y, v[r][0].z, v[r][0].w, v[r][1].x, v[r][1].y, v[r][1].z, v[r][1].w};
#pragma unroll
        for (int i = 0; i < 8; i++) {
          const float lo = bf_lo(w[i]), hi = bf_hi(w[i]);
          mu[r] += lo; rs[r] = fmaf(lo, lo, rs[r]);
          mu[r] += hi; rs[r] = fmaf(hi, hi, rs[r]);
        }
      }
    }
    asm volatile("bar.arrive 4, 512;" ::"f"(mu[0]), "f"(mu[1]), "f"(mu[2]), "f"(mu[3]), "f"(mu[4]) : "memory");
    auto row_consts = [&](float u, int row, bool wr) {
      const float o = __shfl_xor_sync(0xffffffffu, u, 16);
      const float m = ((lane & 16) ? o : u) * (1.f / D_), q = ((lane & 16) ? u : o) * (1.f / D_);
      float k;
      asm("rsqrt.approx.ftz.f32 %0, %1;" : "=f"(k) : "f"(fmaxf(fmaf(-m, m, q), 0.f) + 1e-5f));
      const float kh = bf_lo(pack_bf16(k, k));
      if (wr) asm volatile("st.shared.f32 [%0], %1;" ::"r"(sb + OFF_RATIO + row * 4), "f"(k * rcp(kh)) : "memory");
      return pack_bf16(kh, -m * kh);
    };
    auto row_store = [&](const uint4 (&vr)[2], uint32_t kc, int row) {
      uint32_t khi, c;
      asm("{.reg .b16 l, h; mov.b32 {l, h}, %2; mov.b32 %0, {l, l}; mov.b32 %1, {h, h};}" : "=r"(khi), "=r"(c) : "r"(kc));
#pragma unroll
      for (int h = 0; h < 2; h++)
        sts128(sb + OFF_XA + (h * 4 + (lane >> 3)) * 8192 + row * 128 + (((lane & 7) ^ (row & 7)) << 4),
               hfma2bf(vr[h].x, khi, c), hfma2bf(vr[h].y, khi, c), hfma2bf(vr[h].z, khi, c), hfma2bf(vr[h].w, khi, c));
    };
    {
      float a[4];
#pragma unroll
      for (int r = 0; r < 4; r++) a[r] = ((lane & 16) ? rs[r] : mu[r]) + __shfl_xor_sync(0xffffffffu, (lane & 16) ? mu[r] : rs[r], 16);
#pragma unroll
      for (int r = 0; r < 2; r++) a[r] = ((lane & 8) ? a[2 + r] : a[r]) + __shfl_xor_sync(0xffffffffu, (lane & 8) ? a[r] : a[2 + r], 8);
      float u = ((lane & 4) ? a[1] : a[0]) + __shfl_xor_sync(0xffffffffu, (lane & 4) ? a[0] : a[1], 4);
      u += __shfl_xor_sync(0xffffffffu, u, 2);
      u += __shfl_xor_sync(0xffffffffu, u, 1);
      if (tid == 160) PROF_MARK(14);
      const uint32_t kc = row_consts(u, row4 + ((lane >> 2) & 3), (lane & 19) == 0);
#pragma unroll
      for (int r = 0; r < 4; r++) row_store(v[r], __shfl_sync(0xffffffffu, kc, 4 * r), row4 + r);
    }
    if (five) {
      float u = ((lane & 16) ? rs[4] : mu[4]) + __shfl_xor_sync(0xffffffffu, (lane & 16) ? mu[4] : rs[4], 16);
#pragma unroll
      for (int o = 8; o; o >>= 1) u += __shfl_xor_sync(0xffffffffu, u, o);
      row_store(v[4], row_consts(u, row5, lane == 0), row5);
    }
    sts128(sb + OFF_WKV + tid * 16, wkv.x, wkv.y, wkv.z, wkv.w);
    if (warp == 15) sts128(sb + OFF_WKV + lane * 16, wkv0.x, wkv0.y, wkv0.z, wkv0.w);
    if (tid >= 64) asm volatile("st.shared.f32 [%0], %1;" ::"r"(sb + OFF_B1 + (tid - 64) * 4), "f"(b1v) : "memory");
    if (tid == 160) PROF_MARK(15);
    fence_async_smem();
    bar_sync(0, 512);
  }
  const int wg = warp >> 2, wq = warp & 3;
  if (tid == 160) PROF_MARK(0);

  if (wg == 0) {
    asm volatile("setmaxnreg.dec.sync.aligned.u32 %0;" ::"n"(REG_PROD));
    if (warp == 0 || warp == 3) {
      const int odd = warp & 1;
      uint32_t st = odd;
#define RING_WAIT() mbar_wait(bars + 8 * B_BEMPTY + 8 * (st & 3), (st >> 2) & 1)
#define RING(MAP, ROW, GRP) do { RING_WAIT(); warp_tma(sb + OFF_BR + (st & 3) * 16384, MAP, ROW, GRP, bars + 8 * B_BFULL + 8 * (st & 3)); st += 2; } while (0)
#pragma unroll 1
      for (int i = odd; i < 24; i += 2) RING(&map_w1, 64 * (i & 7), 7 * j + 2 * (i >> 3));
      if (!HELP) {
#pragma unroll 1
        for (int i = odd; i < 4; i += 2) RING(&map_w1t, 128 * i, 7 * j + 6);
      }
#pragma unroll 1
      for (int u = odd; u < NOWN; u += 2) RING(&map_w2, 448 * j + 64 * u, 2 * j);
      const uint32_t epoch = get_epoch();
#define RING_AB(JJ, C) do { RING_WAIT(); \
        warp_tma_ab(sb + OFF_BR + (st & 3) * 16384, &map_w2, 448 * (JJ) + 64 * (C), 2 * j, bars + 8 * B_BFULL + 8 * (st & 3), \
                    sb + OFF_XA + (st & 3) * 8192, g_s.ex + ((rb * 4 + (JJ)) * 9 + (C)) * 512); st += 2; } while (0)
      if (HELP) mbar_wait(bars + 8 * B_XNSENT, 0);
      int c = odd ^ (NOWN & 1);
#pragma unroll 1
      for (int q = 1; q < 4; q++) {
        const int jj = (j + q) & 3;
        poll_flag(g_actflag + (rb * 4 + jj) * 8, epoch);
        fence_async_gmem();
#pragma unroll 1
        for (; c < NOWN; c += 2) RING_AB(jj, c);
        c -= NOWN;
      }
      if (HELP) {
#pragma unroll 1
        for (int jp = 0; jp < 2; jp++) {
          poll_flag(g_s.hflag + (rb * 2 + jp) * 8, epoch);
          fence_async_gmem();
          RING_AB(2 * jp + odd, 6);
        }
      }
#pragma unroll 1
      for (int u = odd; u < 4; u += 2) RING(&map_wo, 128 * ((j + u) & 3), 2 * j);
      if (odd) {
        warp_tma(sb + OFF_XA, &map_wo, 128 * j + 64, 2 * j, bars + 8 * B_QFULL);
        warp_tma(sb + OFF_XA + 16384, &map_wo, 128 * ((j + 1) & 3) + 64, 2 * j, bars + 8 * (B_QFULL + 1));
      }
      mbar_wait(bars + 8 * B_BEMPTY + 8 * odd, 1 ^ PH);
      warp_tma(sb + OFF_BR + odd * 16384, &map_wo, 128 * ((j + 2 + odd) & 3) + 64, 2 * j, bars + 8 * B_BFULL + 8 * odd);
    } else if (warp == 1) {
      const uint32_t epoch = get_epoch();
      float kmax;
      for (uint32_t n = 0;; n++) {
        bool ok = true;
        kmax = 0.f;
#pragma unroll
        for (int i = 0; i < 4; i++) {
          uint32_t e, v;
          asm volatile("ld.relaxed.gpu.global.v2.u32 {%0,%1}, [%2];" : "=r"(e), "=r"(v) : "l"(g_kvflag + (lane + 32 * i) * 4) : "memory");
          ok &= e == epoch;
          const float t = __uint_as_float(v) + __shfl_down_sync(0xffffffffu, __uint_as_float(v), 1);
          if ((lane & 3) == 0) asm("max.NaN.f32 %0, %1, %2;" : "=f"(kmax) : "f"(kmax), "f"(t));
        }
        if (__all_sync(0xffffffffu, ok)) break;
        if (n > 4000000u) __trap();
      }
#pragma unroll
      for (int o = 16; o; o >>= 1) {
        const float t = __shfl_xor_sync(0xffffffffu, kmax, o);
        asm("max.NaN.f32 %0, %1, %2;" : "=f"(kmax) : "f"(kmax), "f"(t));
      }
      if (lane == 0) {
        PROF_MARK(1);
        asm volatile("st.shared.f32 [%0], %1;" ::"r"(sb + OFF_MISC + 32), "f"(kmax) : "memory");
      }
      fence_async_gmem();
      __syncwarp();
      uint32_t slot = 1, par = 1;
#pragma unroll 1
      for (int i = 0; i < 16; i++) {
        if (i == 2) mbar_wait(bars + 8 * B_QDONE, 0);
        if (i >= 3) mbar_wait(bars + 8 * B_KVEMPTY + 8 * slot, par);
        if (i == 15) warp_arrive(bars + 8 * B_LAST, 4);
        warp_bulk_load(sb + OFF_KV + slot * KV_SLOT, g_kv + ((i + (rb >> 1)) & 15) * 512, bars + 8 * B_KVFULL + 8 * slot);
        if (++slot == 3) slot = 0;
        if (slot == 1) par ^= 1;
      }
      if (blockIdx.x == 0) {
        if (HELP) poll_flag(g_s.hflag + ((lane & 2) * 16 + (lane & 1)) * 8, epoch);
        __syncwarp();
        if (lane == 0) st_flag(&g_epoch, epoch);
      }
    } else if (warp == 2) {
      const uint32_t epoch = get_epoch();
      if (lane == 0) l2_prefetch(reinterpret_cast<const uint8_t*>(prm.w1) + blockIdx.x * 14336, 14336);
      mbar_wait(bars + 8 * B_QDONE, 0);
      if (HELP) {
        mbar_wait(bars + 8 * (B_KVFULL + 2), 0);
        warp_bulk_store(g_s.xn + (rb * 8 + 2 * j) * 512, sb + OFF_XA + j * 16384, 16384);
        warp_bulk_store(g_s.ratio + rb * 16 + j * 4, sb + OFF_RATIO + j * 64, 64);
        warp_publish(g_s.xnflag + blockIdx.x * 8, epoch, 0);
        warp_arrive(bars + 8 * B_XNSENT, 4);
      }
      if (lane == 0) {
        l2_prefetch(reinterpret_cast<const uint8_t*>(prm.w2) + blockIdx.x * 14336, 14336);
        l2_prefetch(reinterpret_cast<const uint8_t*>(prm.wo) + blockIdx.x * 4096, 4096);
      }
      __syncwarp();
#pragma unroll 1
      for (int t = 0; t < (HELP ? 3 : 4); t++) {
        mbar_wait(bars + 8 * B_ACTT + 8 * t, 0);
        warp_bulk_store(g_s.ex + (blockIdx.x * 9 + 2 * t) * 512, sb + OFF_ACT + 2 * t * 8192, t < 3 ? 16384 : 8192);
      }
      warp_publish(g_actflag + blockIdx.x * 8, epoch, 0);
      mbar_wait(bars + 8 * B_ACTOWN, 0);
      mbar_wait(bars + 8 * B_LAST, 0);
      if (lane == 0) PROF_MARK(25);
      if (lane < 6) {
        const int sw = lane >= 3, src = rb * 4 + ((j + 1 + lane - 3 * sw) & 3);
        mbar_expect(bars + 8 * (B_OFULL + lane), 8192);
        for (uint32_t n = 0, done = 0; !done; n++) {
          if (ld_flag(g_oflag + (src * 2 + sw) * 8) == epoch) {
            fence_async_gmem();
            bulk_load(sb + OFF_ACT + lane * 8192, g_s.ex + (src * 9 + 7 + sw) * 512, 8192, bars + 8 * (B_OFULL + lane));
            done = 1;
          }
          if (n > 4000000u) __trap();
        }
        if (lane == 5) PROF_MARK(2);
      }
    }
  } else if (wg == 1) {
    asm volatile("setmaxnreg.dec.sync.aligned.u32 %0;" ::"n"(REG_GEMM));
    const int tid = fresh_tid(), lane = tid & 31;
    const int g = lane >> 2, t4 = lane & 3;
    float ratio0, ratio1;
    asm volatile("ld.shared.f32 %0, [%1];" : "=f"(ratio0) : "r"(sb + OFF_RATIO + (wq * 16 + g) * 4));
    asm volatile("ld.shared.f32 %0, [%1];" : "=f"(ratio1) : "r"(sb + OFF_RATIO + (wq * 16 + g + 8) * 4));
    {
      float kv[4] = {0.f, 0.f, 0.f, 0.f};
      fence_regs(kv);
      const uint64_t da = desc_a(sb + OFF_XA), db = mkdesc(sb + OFF_WKV, 128, 128, 0);
#pragma unroll 1
      for (int c = 0; c < 8; c++) {
        WG_FENCE();
#pragma unroll
        for (int kk = 0; kk < 4; kk++) wgmma_ss_n8_tb(kv, da + c * 512 + kk * 2, db + c * 64 + kk * 16, 1);
        WG_COMMIT();
      }
      if (tid == 128) PROF_MARK(17);
      WG_WAIT(0);
      fence_regs(kv);
      if (tid == 128) PROF_MARK(18);
      const uint32_t p0 = pack_bf16(kv[0] * ratio0, kv[1] * ratio0), p1 = pack_bf16(kv[2] * ratio1, kv[3] * ratio1);
      asm volatile("st.shared.u32 [%0], %1;" ::"r"(sb + OFF_KVO + (wq * 16 + g) * 16 + t4 * 4), "r"(p0) : "memory");
      asm volatile("st.shared.u32 [%0], %1;" ::"r"(sb + OFF_KVO + (wq * 16 + g + 8) * 16 + t4 * 4), "r"(p1) : "memory");
      fence_async_smem();
      bar_sync(1, 128);
      if (wq == 0) warp_bulk_store(g_kv + (rb >> 1) * 512 + j * 128 + (rb & 1) * 64, sb + OFF_KVO, 1024);
      if (tid == 128) PROF_MARK(19);
      warp_arrive(bars + 8 * B_KVMMA);
      float n0 = bf_lo(p0) * bf_lo(p0) + bf_hi(p0) * bf_hi(p0), n1 = bf_lo(p1) * bf_lo(p1) + bf_hi(p1) * bf_hi(p1);
      n0 += __shfl_xor_sync(0xffffffffu, n0, 1); n1 += __shfl_xor_sync(0xffffffffu, n1, 1);
      n0 += __shfl_xor_sync(0xffffffffu, n0, 2); n1 += __shfl_xor_sync(0xffffffffu, n1, 2);
      asm("max.NaN.f32 %0, %1, %2;" : "=f"(n0) : "f"(n0), "f"(n1));
#pragma unroll
      for (int o = 4; o < 32; o <<= 1) {
        const float t = __shfl_xor_sync(0xffffffffu, n0, o);
        asm("max.NaN.f32 %0, %1, %2;" : "=f"(n0) : "f"(n0), "f"(t));
      }
      if (lane == 0) asm volatile("st.shared.f32 [%0], %1;" ::"r"(sb + OFF_MISC + 16 + wq * 4), "f"(n0) : "memory");
      bar_sync(1, 128);
      if (wq == 0) {
        float m0, m1, m2, m3;
        asm volatile("ld.shared.v4.f32 {%0,%1,%2,%3}, [%4];" : "=f"(m0), "=f"(m1), "=f"(m2), "=f"(m3) : "r"(sb + OFF_MISC + 16) : "memory");
        asm("max.NaN.f32 %0, %1, %2;" : "=f"(m0) : "f"(m0), "f"(m1));
        asm("max.NaN.f32 %0, %1, %2;" : "=f"(m2) : "f"(m2), "f"(m3));
        asm("max.NaN.f32 %0, %1, %2;" : "=f"(m0) : "f"(m0), "f"(m2));
        warp_publish(g_kvflag + blockIdx.x * 4, get_epoch(), __float_as_uint(m0));
      }
      if (tid == 128) PROF_MARK(3);
    }
    float acc[64];
#pragma unroll
    for (int i = 0; i < 64; i++) acc[i] = 0.f;
    const uint32_t st_row = wq * 16 + (lane & 7) + ((lane >> 3) & 1) * 8;
    const uint64_t dxa = desc_a(sb + OFF_XA), dact = desc_a(sb + OFF_ACT), dbr = desc_b(sb + OFF_BR);
#define WAIT_B(slot, par) mbar_wait(bars + 8 * B_BFULL + 8 * (slot), par)
#define REL_B(i) warp_arrive(bars + 8 * B_BEMPTY + 8 * ((i) & 3), 2)
    mbar_wait(bars + 8 * B_QDONE, 0);
#pragma unroll 1
    for (int t = 0; t < (HELP ? 3 : 4); t++) {
      fence_regs(acc);
      if (HELP || t < 3) {
        WAIT_B(0, 1);
        GEMM_CHUNK(G1DEPTH, wgmma_ss_n128_tb, acc, dxa, dbr, true, );
#pragma unroll
        for (uint32_t c = 1; c < 8; c++) {
          WAIT_B(c & 3, (c >> 2) ^ 1);
          GEMM_CHUNK(G1DEPTH, wgmma_ss_n128_tb, acc, dxa + c * 512, dbr + (c & 3) * 1024, false, REL_B(c - 1));
        }
      } else {
        float (&acc32)[32] = *reinterpret_cast<float (*)[32]>(&acc[0]);
#pragma unroll
        for (int i = 0; i < 32; i++) acc32[i] = 0.f;
        fence_regs(acc32);
#pragma unroll
        for (uint32_t c = 0; c < 4; c++) {
          WAIT_B(c, 1);
          GEMM_CHUNK(G1DEPTH, wgmma_ss_n64_tb, acc32, dxa + c * 1024, dbr + c * 1024, false, if (c > 0) REL_B(c - 1));
          GEMM_CHUNK(G1DEPTH, wgmma_ss_n64_tb, acc32, dxa + c * 1024 + 512, dbr + c * 1024 + 512, false, );
        }
      }
      WG_WAIT(0);
      fence_regs(acc);
      REL_B(3);
      const uint32_t b1a = sb + OFF_B1 + t * 512 + t4 * 8;
      const uint32_t sta = sb + OFF_ACT + t * 16384 + st_row * 128, stx = ((lane >> 4) ^ (st_row & 7)) << 4;
      mish_store<8>(acc, ratio0, ratio1, b1a, sta, stx);
      if (HELP || t < 3) mish_store<8>(*reinterpret_cast<float (*)[64]>(&acc[32]), ratio0, ratio1, b1a + 256, sta + 8192, stx);
      fence_async_smem();
      __syncwarp();
      warp_arrive(bars + 8 * B_ACTT + 8 * t);
    }
    if (tid == 128) PROF_MARK(4);
    {
      const uint32_t* xp = reinterpret_cast<const uint32_t*>(prm.x + (size_t)(rb * 64 + wq * 16 + g) * D_ + 128 * j) + t4;
#pragma unroll
      for (int c = 0; c < 16; c++) {
        const uint32_t a = __ldg(xp + c * 4), b = __ldg(xp + 8 * (D_ / 2) + c * 4);
        acc[4 * c] = bf_lo(a); acc[4 * c + 1] = bf_hi(a); acc[4 * c + 2] = bf_lo(b); acc[4 * c + 3] = bf_hi(b);
      }
    }
    bar_sync(1, 128);
    fence_regs(acc);
#pragma unroll 4
    for (uint32_t u = 0; u < 28; u++) {
      WAIT_B(u & 3, ((u >> 2) & 1) ^ PH);
      GEMM_CHUNK(G2DEPTH, wgmma_ss_n128_tb, acc, u < NOWN ? dact + u * 512 : dxa + (u & 3) * 512, dbr + (u & 3) * 1024, false,
                 if (u > 0) REL_B(u - 1); if (u == NOWN) warp_arrive(bars + 8 * B_ACTOWN));
    }
    WG_WAIT(0);
    REL_B(3);
    if (tid == 128) PROF_MARK(5);
    __nv_bfloat16* outp = prm.out + (size_t)(rb * 64 + wq * 16 + (lane >> 4)) * D_ + 128 * j + (lane & 15) * 8;
    uint32_t sta = sb + OFF_XA + 6 * 8192 + wq * 4096 + (st_row & 15) * 256 + (((lane >> 4) ^ (st_row & 7)) << 4);
    uint32_t lda = sb + OFF_XA + 6 * 8192 + wq * 4096 + (lane >> 4) * 256 + (((lane & 15) ^ (lane >> 4)) << 4);
    asm volatile("" : "+l"(outp), "+r"(sta), "+r"(lda));
#pragma unroll 1
    for (uint32_t u = 0; u < 8; u++) {
      const uint32_t bs = u < 6 ? u : u - 6, rem = u < 4 ? u - 1 : u - 2;
      mbar_wait(bars + 8 * B_BFULL + 8 * bs, u < 4 ? 1 ^ PH : u < 6 ? 1 : PH);
      mbar_wait((u & 3) ? bars + 8 * B_OFULL + 8 * rem : bars + 8 * B_OOWN + 2 * u, 0);
      const uint64_t da = (u & 3) ? dact + rem * 512 : dxa + 2048 + u * 128, db = (bs < 4 ? dbr : dbr - 8192) + bs * 1024;
      WG_FENCE();
#pragma unroll
      for (int kk = 0; kk < 4; kk++) wgmma_ss_n128_tb(acc, da + kk * 2, db + kk * 128, 1);
      WG_COMMIT();
      if (u < 2) { WG_WAIT(0); REL_B(u); }
    }
    WG_WAIT(0);
    fence_regs(acc);
    if (tid == 128) PROF_MARK(6);
    {
#pragma unroll
      for (int c = 0; c < 16; c += 2)
        stsm_x4(sta ^ (c << 4), pack_bf16(acc[4 * c], acc[4 * c + 1]), pack_bf16(acc[4 * c + 2], acc[4 * c + 3]),
                pack_bf16(acc[4 * c + 4], acc[4 * c + 5]), pack_bf16(acc[4 * c + 6], acc[4 * c + 7]));
      __syncwarp();
#pragma unroll
      for (int i = 0; i < 8; i++) {
        uint4 v;
        asm volatile("ld.shared.v4.u32 {%0,%1,%2,%3}, [%4];" : "=r"(v.x), "=r"(v.y), "=r"(v.z), "=r"(v.w)
                     : "r"((lda ^ ((2 * i & 7) << 4)) + i * 512) : "memory");
        asm volatile("st.global.v4.u32 [%0], {%1,%2,%3,%4};" ::"l"(outp + 2 * i * D_), "r"(v.x), "r"(v.y), "r"(v.z), "r"(v.w) : "memory");
      }
    }
    if (tid == 128) PROF_MARK(7);
  } else {
    asm volatile("setmaxnreg.inc.sync.aligned.u32 %0;" ::"n"(REG_ATT));
    int tid = fresh_tid(), lane = tid & 31;
    const int w = wg - 2;
    float sx[32], sy[32], o[4][12];
    uint32_t q[4][4], pa[16], pb[16];
#pragma unroll
    for (int i = 0; i < 32; i++) { sx[i] = 0.f; sy[i] = 0.f; }
    if (w == 0) {
      float sq[64];
#pragma unroll
      for (int i = 0; i < 64; i++) sq[i] = 0.f;
      float sc0, sc1;
      asm volatile("ld.shared.f32 %0, [%1];" : "=f"(sc0) : "r"(sb + OFF_RATIO + (wq * 16 + (lane >> 2)) * 4));
      asm volatile("ld.shared.f32 %0, [%1];" : "=f"(sc1) : "r"(sb + OFF_RATIO + (wq * 16 + (lane >> 2) + 8) * 4));
      sc0 *= 0.25f * 1.4426950408889634f; sc1 *= 0.25f * 1.4426950408889634f;
      mbar_wait(bars + 8 * B_KVMMA, 0);
      fence_regs(sq);
      constexpr uint64_t da = desc_a(sb + OFF_XA), db = desc_b(sb + OFF_BR);
#pragma unroll 1
      for (int c = 0; c < 8; c++) {
        mbar_wait(bars + 8 * c, 0);
        WG_FENCE();
#pragma unroll
        for (int kk = 0; kk < 4; kk++) wgmma_ss_n128_tb(sq, da + c * 512 + kk * 2, db + c * 1024 + kk * 128, 1);
        WG_COMMIT(); WG_WAIT(1);
        if (c > 0 && c <= 4) warp_arrive(bars + 8 * B_BEMPTY + 8 * (c - 1), 2);
      }
      WG_WAIT(0);
      fence_regs(sq);
      warp_arrive(bars + 8 * B_QDONE, 2);
#pragma unroll
      for (int t = 0; t < 4; t++)
        sts128(sb + OFF_WKV + t * 2048 + (tid & 127) * 16, pack_bf16(sq[32 + 8 * t] * sc0, sq[33 + 8 * t] * sc0),
               pack_bf16(sq[34 + 8 * t] * sc1, sq[35 + 8 * t] * sc1), pack_bf16(sq[36 + 8 * t] * sc0, sq[37 + 8 * t] * sc0),
               pack_bf16(sq[38 + 8 * t] * sc1, sq[39 + 8 * t] * sc1));
      asm volatile("bar.arrive 6, 256;" ::: "memory");
#pragma unroll
      for (int t = 0; t < 4; t++)
#pragma unroll
        for (int i = 0; i < 4; i++) {
          const float sc = (i & 1) ? sc1 : sc0;
          q[t][i] = pack_bf16(sq[8 * t + 2 * i] * sc, sq[8 * t + 2 * i + 1] * sc);
        }
    } else {
      bar_sync(6, 256);
#pragma unroll
      for (int t = 0; t < 4; t++)
        asm volatile("ld.shared.v4.u32 {%0,%1,%2,%3}, [%4];" : "=r"(q[t][0]), "=r"(q[t][1]), "=r"(q[t][2]), "=r"(q[t][3])
                     : "r"(sb + OFF_WKV + t * 2048 + (tid & 127) * 16) : "memory");
    }
    float qmax = 0.f;
#pragma unroll
    for (int t = 0; t < 4; t++) {
      float n0 = 0.f, n1 = 0.f;
#pragma unroll
      for (int i = 0; i < 4; i++) {
        const float n = bf_lo(q[t][i]) * bf_lo(q[t][i]) + bf_hi(q[t][i]) * bf_hi(q[t][i]);
        if (i & 1) n1 += n; else n0 += n;
      }
      n0 += __shfl_xor_sync(0xffffffffu, n0, 1); n1 += __shfl_xor_sync(0xffffffffu, n1, 1);
      n0 += __shfl_xor_sync(0xffffffffu, n0, 2); n1 += __shfl_xor_sync(0xffffffffu, n1, 2);
      asm("max.NaN.f32 %0, %1, %2;" : "=f"(n0) : "f"(n0), "f"(n1));
      asm("max.NaN.f32 %0, %1, %2;" : "=f"(qmax) : "f"(qmax), "f"(n0));
#pragma unroll
      for (int i = 0; i < 12; i++) o[t][i] = 0.f;
    }
    if (tid == 256) PROF_MARK(8);
    mbar_wait(bars + 8 * (B_KVFULL + 1), 0);
    uint32_t safe;
    {
      float kmax;
      asm volatile("ld.shared.f32 %0, [%1];" : "=f"(kmax) : "r"(sb + OFF_MISC + 32) : "memory");
      const uint32_t ok = (qmax * kmax <= 3600.f) ? 1u : 0u;
      asm volatile("{.reg .pred p, r; setp.ne.u32 p, %1, 0; bar.red.and.pred r, %2, 128, p; selp.u32 %0, 1, 0, r;}"
                   : "=r"(safe) : "r"(ok), "r"(2 + w) : "memory");
      safe = __shfl_sync(0xffffffffu, safe, 0);
    }
    if (tid == 256) PROF_MARK(9);
    const uint64_t dk0 = mkdesc(sb + OFF_KV, 2048, 128, 0), dv0 = mkdesc(sb + OFF_KV + 4096, 128, 2048, 0);
#pragma unroll
    for (int t = 0; t < 4; t++) { fence_regs(o[t]); fence_regs(q[t]); }
    fence_regs(sx); fence_regs(sy);
#define QK(S, T, DK) wgmma_rs_n64(S, q[T][0], q[T][1], q[T][2], q[T][3], DK, 0)
    if (safe) {
      uint32_t slot = 1, prev = 0, par = 0;
      if (SKEW && w == 1) mbar_wait(bars + 8 * B_SKEW, 0);
      for (int it = 0; it < 16; it++) {
        mbar_wait(bars + 8 * B_KVFULL + 8 * slot, par);
        const uint64_t dk = dk0 + slot * (KV_SLOT >> 4), dv = dv0 + slot * (KV_SLOT >> 4);
        WG_FENCE();
        QK(sx, 0, dk); WG_COMMIT();
        QK(sy, 1, dk); WG_COMMIT();
        WG_WAIT(1);
        if (it > 0) warp_arrive(bars + 8 * B_KVEMPTY + 8 * prev);
#pragma unroll
        for (int s = 0; s < 8; s += 2) {
          if (SKEW && s == (SKEW & 7) && it == (SKEW >> 3) && w == 0) warp_arrive(bars + 8 * B_SKEW);
          if (s == 0) attn_step<-1>(sx, pa, o[0], dv);
          else attn_step<5>(sx, pa, o[s & 3], dv + (s >> 2) * 64);
          if (s + 2 < 8) {
            QK(sx, (s + 2) & 3, dk + ((s + 2) >> 2) * 64); WG_COMMIT();
            attn_step<5>(sy, pb, o[(s + 1) & 3], dv + (s >> 2) * 64);
            QK(sy, (s + 3) & 3, dk + ((s + 3) >> 2) * 64); WG_COMMIT();
          } else {
            attn_step<4>(sy, pb, o[3], dv + 64);
          }
        }
        prev = slot;
        if (++slot == 3) slot = 0;
        if (slot == 1) par ^= 1;
      }
      WG_WAIT(0);
    } else {
      if (SKEW && w == 0) warp_arrive(bars + 8 * B_SKEW);
      float m[4][2];
#pragma unroll
      for (int t = 0; t < 4; t++) m[t][0] = m[t][1] = -INFINITY;
      uint32_t slot = 1, par = 0;
      for (int it = 0; it < 16; it++) {
        mbar_wait(bars + 8 * B_KVFULL + 8 * slot, par);
        for (int h = 0; h < 2; h++) {
          const uint64_t dk = dk0 + slot * (KV_SLOT >> 4) + h * 64, dv = dv0 + slot * (KV_SLOT >> 4) + h * 64;
#pragma unroll
          for (int t = 0; t < 4; t++) {
            WG_FENCE();
            QK(sx, t, dk); WG_COMMIT(); WG_WAIT(0);
            fence_regs(sx);
            float m0 = m[t][0], m1 = m[t][1];
#pragma unroll
            for (int i = 0; i < 8; i++) {
              m0 = fmaxf(m0, fmaxf(sx[4 * i], sx[4 * i + 1]));
              m1 = fmaxf(m1, fmaxf(sx[4 * i + 2], sx[4 * i + 3]));
            }
            m0 = fmaxf(m0, __shfl_xor_sync(0xffffffffu, m0, 1)); m1 = fmaxf(m1, __shfl_xor_sync(0xffffffffu, m1, 1));
            m0 = fmaxf(m0, __shfl_xor_sync(0xffffffffu, m0, 2)); m1 = fmaxf(m1, __shfl_xor_sync(0xffffffffu, m1, 2));
            const float a0 = ex2(m[t][0] - m0), a1 = ex2(m[t][1] - m1);
            m[t][0] = m0; m[t][1] = m1;
#pragma unroll
            for (int i = 0; i < 12; i++) o[t][i] *= (i & 2) ? a1 : a0;
#pragma unroll
            for (int i = 0; i < 16; i++) {
              const float mm = (i & 1) ? m1 : m0;
              pa[i] = pack_bf16(ex2(sx[2 * i] - mm), ex2(sx[2 * i + 1] - mm));
            }
            fence_regs(pa); fence_regs(o[t]);
            WG_FENCE();
#pragma unroll
            for (int c = 0; c < 4; c++) wgmma_rs_n24_tb(o[t], pa[4 * c], pa[4 * c + 1], pa[4 * c + 2], pa[4 * c + 3], dv + c * 16, 1);
            WG_COMMIT(); WG_WAIT(0);
            fence_regs(o[t]);
          }
        }
        warp_arrive(bars + 8 * B_KVEMPTY + 8 * slot);
        if (++slot == 3) slot = 0;
        if (slot == 1) par ^= 1;
      }
    }
#pragma unroll
    for (int t = 0; t < 4; t++) fence_regs(o[t]);
    if (tid == 256) PROF_MARK(10);
    if (tid == 384) PROF_MARK(11);
    tid = fresh_tid(); lane = tid & 31;
    mbar_wait(bars + 8 * (B_ACTT + (HELP ? 2 : 3)), 0);
    const uint32_t st_row = wq * 16 + (lane & 7) + ((lane >> 3) & 1) * 8;
#pragma unroll
    for (int t = 0; t < 4; t++) {
      const float r0 = rcp(o[t][8]), r1 = rcp(o[t][10]);
      const uint32_t unit = 2 * t + (lane >> 4);
      stsm_x4(sb + OFF_XA + (4 + w) * 8192 + st_row * 128 + ((unit ^ (st_row & 7)) << 4),
              pack_bf16(o[t][0] * r0, o[t][1] * r0), pack_bf16(o[t][2] * r1, o[t][3] * r1),
              pack_bf16(o[t][4] * r0, o[t][5] * r0), pack_bf16(o[t][6] * r1, o[t][7] * r1));
    }
    fence_async_smem();
    __syncwarp();
    warp_arrive(bars + 8 * B_OOWN + 8 * w);
    warp_bulk_store(g_s.ex + (blockIdx.x * 9 + 7 + w) * 512 + wq * 128, sb + OFF_XA + (4 + w) * 8192 + wq * 2048, 2048);
    if (tid == 256) PROF_MARK(22);
    const uint32_t epoch = get_epoch();
    asm volatile("cp.async.bulk.wait_group 0;" ::: "memory");
    bar_sync(2 + w, 128);
    if ((tid & 127) == 0) st_flag(g_oflag + (blockIdx.x * 2 + w) * 8, epoch);
    if (tid == 256) PROF_MARK(23);
  }
}

typedef CUresult (*EncodeFn)(CUtensorMap*, CUtensorMapDataType, cuuint32_t, void*, const cuuint64_t*, const cuuint64_t*,
                             const cuuint32_t*, const cuuint32_t*, CUtensorMapInterleave, CUtensorMapSwizzle,
                             CUtensorMapL2promotion, CUtensorMapFloatOOBfill);

void make_map(EncodeFn fn, CUtensorMap* m, const void* p, uint64_t rows, uint64_t cols, uint32_t box_rows, uint32_t box_groups) {
  const cuuint64_t dims[3] = {64, rows, cols / 64};
  const cuuint64_t strides[2] = {cols * 2, 128};
  const cuuint32_t box[3] = {64, box_rows, box_groups}, es[3] = {1, 1, 1};
  fn(m, CU_TENSOR_MAP_DATA_TYPE_BFLOAT16, 3, const_cast<void*>(p), dims, strides, box, es, CU_TENSOR_MAP_INTERLEAVE_NONE,
     CU_TENSOR_MAP_SWIZZLE_128B, CU_TENSOR_MAP_L2_PROMOTION_L2_128B, CU_TENSOR_MAP_FLOAT_OOB_FILL_NONE);
}

}

extern "C" void kernel_launch(void* const* d_in, const int* in_sizes, int n_in, void* d_out, int out_size) {
  (void)in_sizes; (void)n_in; (void)out_size;
  void* fnp = nullptr;
  cudaDriverEntryPointQueryResult qr;
  cudaGetDriverEntryPoint("cuTensorMapEncodeTiled", &fnp, cudaEnableDefault, &qr);
  EncodeFn fn = reinterpret_cast<EncodeFn>(fnp);
  CUtensorMap mq, m1, m1t, m2, mo;
  make_map(fn, &mq, d_in[1], D_, D_, 64, 2);
  make_map(fn, &m1, d_in[6], D_, F_, 64, 2);
  make_map(fn, &m1t, d_in[6], D_, F_, 128, 1);
  make_map(fn, &m2, d_in[8], F_, D_, 64, 2);
  make_map(fn, &mo, d_in[4], D_, D_, 64, 2);
  Params p;
  p.x = (const __nv_bfloat16*)d_in[0]; p.wq = (const __nv_bfloat16*)d_in[1]; p.wk = (const __nv_bfloat16*)d_in[2]; p.wv = (const __nv_bfloat16*)d_in[3];
  p.b1 = (const __nv_bfloat16*)d_in[7]; p.w1 = (const __nv_bfloat16*)d_in[6]; p.w2 = (const __nv_bfloat16*)d_in[8];
  p.wo = (const __nv_bfloat16*)d_in[4]; p.out = (__nv_bfloat16*)d_out;
  int dev = 0, sms = 0;
  cudaGetDevice(&dev);
  cudaDeviceGetAttribute(&sms, cudaDevAttrMultiProcessorCount, dev);
  if (USE_HELP && sms >= NCTA + 4) {
    cudaFuncSetAttribute(fused_kernel<true>, cudaFuncAttributeMaxDynamicSharedMemorySize, SMEM_BYTES);
    fused_kernel<true><<<NCTA + 4, 512, SMEM_BYTES>>>(p, mq, m1, m1t, m2, mo);
  } else {
    cudaFuncSetAttribute(fused_kernel<false>, cudaFuncAttributeMaxDynamicSharedMemorySize, SMEM_BYTES);
    fused_kernel<false><<<NCTA, 512, SMEM_BYTES>>>(p, mq, m1, m1t, m2, mo);
  }
}
```

```cpp
#include <cuda_runtime.h>
#include <cuda_bf16.h>
#include <cuda.h>
#include <stdint.h>

#pragma nv_diag_suppress 550

namespace {

constexpr int D_ = 512, F_ = 1792;
constexpr int NCTA = 128;

#define G1DEPTH 2
#define G2DEPTH 1
#define USE_HELP 1
#define SKEW 8
#define POLY_MASK 0xB755u
constexpr int REG_ATT = 192, REG_GEMM = 104, REG_PROD = 24;
static_assert(2 * REG_ATT + REG_GEMM + REG_PROD <= 512, "register pool");

constexpr uint32_t OFF_XA  = 0;
constexpr uint32_t OFF_BR  = 65536;
constexpr uint32_t OFF_ACT = OFF_BR + 65536;
constexpr uint32_t OFF_KV  = OFF_ACT + 57344;
constexpr uint32_t OFF_WKV = OFF_KV + 30720;
constexpr uint32_t OFF_B1  = OFF_WKV + 8192;
constexpr uint32_t OFF_KVO = OFF_B1 + 1792;
constexpr uint32_t OFF_RATIO = OFF_KVO + 1024;
constexpr uint32_t OFF_BAR = OFF_RATIO + 256;
constexpr uint32_t SMEM_BYTES = OFF_BAR + 640 + 1024;
static_assert(SMEM_BYTES <= 232448, "smem");
constexpr uint32_t KV_SLOT = 10240;

enum : uint32_t {
  B_BFULL = 0, B_QFULL = 4, B_HFULL = 8  , B_OHINT = 8, B_KMAX = 10, B_KVFULL = 12, B_OFULL = 15,
  B_BEMPTY = 21, B_KVEMPTY = 25, B_QDONE = 28,
  B_OOWN = 29, B_LAST = 31, B_ACTOWN = 32, B_ACTT = 33, B_XNSENT = 37, B_KVMMA = 38, B_SKEW = 39,
  B_KVCHK = 40, B_OCHK = 41, B_OMMA = 42, B_OFIX = 43,
  B_EPOCH = 44, B_COUNT = 45
};
constexpr uint32_t OFF_MISC = OFF_BAR + 8 * 50;

struct __align__(1024) Scratch {
  uint4    kv[2][16 * 512];
  uint2    kvflag[NCTA * 4];
  uint32_t kvflag2[NCTA * 8];
  uint32_t oflag[NCTA * 2 * 8];
  uint32_t oflag2[NCTA * 2 * 8];
  uint32_t actflag[NCTA * 8];
  uint32_t xnflag[NCTA * 8];
  uint32_t hflag[64 * 8];
  __align__(32) uint32_t epoch;
  uint32_t pad[255];
  uint4    ratio[32 * 16];
  uint4    xn[32 * 8 * 512];
  uint4    ex[NCTA * 11 * 512];
};
__device__ Scratch g_s;
#define g_kvflag g_s.kvflag
#define g_oflag g_s.oflag
#define g_actflag g_s.actflag
#define g_epoch g_s.epoch

#define WG_FENCE()  asm volatile("wgmma.fence.sync.aligned;" ::: "memory")
#define WG_COMMIT() asm volatile("wgmma.commit_group.sync.aligned;" ::: "memory")
#define WG_WAIT(n)  asm volatile("wgmma.wait_group.sync.aligned %0;" ::"n"(n) : "memory")

__device__ __forceinline__ void wgmma_ss_n8_tb(float (&d)[4], uint64_t da, uint64_t db, int sd) {
  asm volatile("{.reg .pred p; setp.ne.b32 p, %6, 0;\n"
      "wgmma.mma_async.sync.aligned.m64n8k16.f32.bf16.bf16 {"
      "%0, %1, %2, %3"
      "}, %4, %5, p, 1, 1, 0, 1;}\n"
      : "+f"(d[0]), "+f"(d[1]), "+f"(d[2]), "+f"(d[3])
      : "l"(da), "l"(db), "r"(sd));
}
__device__ __forceinline__ void wgmma_ss_n64_tb(float (&d)[32], uint64_t da, uint64_t db, int sd) {
  asm volatile("{.reg .pred p; setp.ne.b32 p, %34, 0;\n"
      "wgmma.mma_async.sync.aligned.m64n64k16.f32.bf16.bf16 {"
      "%0, %1, %2, %3, %4, %5, %6, %7, %8, %9, %10, %11, %12, %13, %14, %15,"
      "%16, %17, %18, %19, %20, %21, %22, %23, %24, %25, %26, %27, %28, %29, %30, %31"
      "}, %32, %33, p, 1, 1, 0, 1;}\n"
      : "+f"(d[0]), "+f"(d[1]), "+f"(d[2]), "+f"(d[3]), "+f"(d[4]), "+f"(d[5]), "+f"(d[6]), "+f"(d[7]),
        "+f"(d[8]), "+f"(d[9]), "+f"(d[10]), "+f"(d[11]), "+f"(d[12]), "+f"(d[13]), "+f"(d[14]), "+f"(d[15]),
        "+f"(d[16]), "+f"(d[17]), "+f"(d[18]), "+f"(d[19]), "+f"(d[20]), "+f"(d[21]), "+f"(d[22]), "+f"(d[23]),
        "+f"(d[24]), "+f"(d[25]), "+f"(d[26]), "+f"(d[27]), "+f"(d[28]), "+f"(d[29]), "+f"(d[30]), "+f"(d[31])
      : "l"(da), "l"(db), "r"(sd));
}
__device__ __forceinline__ void wgmma_ss_n128_tb(float (&d)[64], uint64_t da, uint64_t db, int sd) {
  asm volatile("{.reg .pred p; setp.ne.b32 p, %66, 0;\n"
      "wgmma.mma_async.sync.aligned.m64n128k16.f32.bf16.bf16 {"
      "%0, %1, %2, %3, %4, %5, %6, %7, %8, %9, %10, %11, %12, %13, %14, %15,"
      "%16, %17, %18, %19, %20, %21, %22, %23, %24, %25, %26, %27, %28, %29, %30, %31,"
      "%32, %33, %34, %35, %36, %37, %38, %39, %40, %41, %42, %43, %44, %45, %46, %47,"
      "%48, %49, %50, %51, %52, %53, %54, %55, %56, %57, %58, %59, %60, %61, %62, %63"
      "}, %64, %65, p, 1, 1, 0, 1;}\n"
      : "+f"(d[0]), "+f"(d[1]), "+f"(d[2]), "+f"(d[3]), "+f"(d[4]), "+f"(d[5]), "+f"(d[6]), "+f"(d[7]),
        "+f"(d[8]), "+f"(d[9]), "+f"(d[10]), "+f"(d[11]), "+f"(d[12]), "+f"(d[13]), "+f"(d[14]), "+f"(d[15]),
        "+f"(d[16]), "+f"(d[17]), "+f"(d[18]), "+f"(d[19]), "+f"(d[20]), "+f"(d[21]), "+f"(d[22]), "+f"(d[23]),
        "+f"(d[24]), "+f"(d[25]), "+f"(d[26]), "+f"(d[27]), "+f"(d[28]), "+f"(d[29]), "+f"(d[30]), "+f"(d[31]),
        "+f"(d[32]), "+f"(d[33]), "+f"(d[34]), "+f"(d[35]), "+f"(d[36]), "+f"(d[37]), "+f"(d[38]), "+f"(d[39]),
        "+f"(d[40]), "+f"(d[41]), "+f"(d[42]), "+f"(d[43]), "+f"(d[44]), "+f"(d[45]), "+f"(d[46]), "+f"(d[47]),
        "+f"(d[48]), "+f"(d[49]), "+f"(d[50]), "+f"(d[51]), "+f"(d[52]), "+f"(d[53]), "+f"(d[54]), "+f"(d[55]),
        "+f"(d[56]), "+f"(d[57]), "+f"(d[58]), "+f"(d[59]), "+f"(d[60]), "+f"(d[61]), "+f"(d[62]), "+f"(d[63])
      : "l"(da), "l"(db), "r"(sd));
}
__device__ __forceinline__ void wgmma_rs_n64(float (&d)[32], uint32_t a0, uint32_t a1, uint32_t a2, uint32_t a3, uint64_t db, int sd) {
  asm volatile("{.reg .pred p; setp.ne.b32 p, %37, 0;\n"
      "wgmma.mma_async.sync.aligned.m64n64k16.f32.bf16.bf16 {"
      "%0, %1, %2, %3, %4, %5, %6, %7, %8, %9, %10, %11, %12, %13, %14, %15,"
      "%16, %17, %18, %19, %20, %21, %22, %23, %24, %25, %26, %27, %28, %29, %30, %31"
      "}, {%32,%33,%34,%35}, %36, p, 1, 1, 0;}\n"
      : "+f"(d[0]), "+f"(d[1]), "+f"(d[2]), "+f"(d[3]), "+f"(d[4]), "+f"(d[5]), "+f"(d[6]), "+f"(d[7]),
        "+f"(d[8]), "+f"(d[9]), "+f"(d[10]), "+f"(d[11]), "+f"(d[12]), "+f"(d[13]), "+f"(d[14]), "+f"(d[15]),
        "+f"(d[16]), "+f"(d[17]), "+f"(d[18]), "+f"(d[19]), "+f"(d[20]), "+f"(d[21]), "+f"(d[22]), "+f"(d[23]),
        "+f"(d[24]), "+f"(d[25]), "+f"(d[26]), "+f"(d[27]), "+f"(d[28]), "+f"(d[29]), "+f"(d[30]), "+f"(d[31])
      : "r"(a0), "r"(a1), "r"(a2), "r"(a3), "l"(db), "r"(sd));
}
__device__ __forceinline__ void wgmma_rs_n24_tb(float (&d)[12], uint32_t a0, uint32_t a1, uint32_t a2, uint32_t a3, uint64_t db, int sd) {
  asm volatile("{.reg .pred p; setp.ne.b32 p, %17, 0;\n"
      "wgmma.mma_async.sync.aligned.m64n24k16.f32.bf16.bf16 {"
      "%0, %1, %2, %3, %4, %5, %6, %7, %8, %9, %10, %11"
      "}, {%12,%13,%14,%15}, %16, p, 1, 1, 1;}\n"
      : "+f"(d[0]), "+f"(d[1]), "+f"(d[2]), "+f"(d[3]), "+f"(d[4]), "+f"(d[5]), "+f"(d[6]), "+f"(d[7]),
        "+f"(d[8]), "+f"(d[9]), "+f"(d[10]), "+f"(d[11])
      : "r"(a0), "r"(a1), "r"(a2), "r"(a3), "l"(db), "r"(sd));
}

template <int N> __device__ __forceinline__ void fence_regs(float (&a)[N]) {
#pragma unroll
  for (int i = 0; i < N; i++) asm volatile("" : "+f"(a[i])::"memory");
}
template <int N> __device__ __forceinline__ void fence_regs(uint32_t (&a)[N]) {
#pragma unroll
  for (int i = 0; i < N; i++) asm volatile("" : "+r"(a[i])::"memory");
}
__host__ __device__ constexpr uint64_t mkdesc(uint32_t addr, uint32_t lbo, uint32_t sbo, uint32_t swz) {
  return (uint64_t)((addr & 0x3FFFF) >> 4) | ((uint64_t)(lbo >> 4) << 16) | ((uint64_t)(sbo >> 4) << 32) | ((uint64_t)swz << 62);
}
__host__ __device__ constexpr uint64_t desc_a(uint32_t addr) { return mkdesc(addr, 16, 1024, 1); }
__host__ __device__ constexpr uint64_t desc_b(uint32_t addr) { return mkdesc(addr, 8192, 1024, 1); }

__device__ __forceinline__ void mbar_init(uint32_t bar, uint32_t cnt) {
  asm volatile("mbarrier.init.shared::cta.b64 [%0], %1;" ::"r"(bar), "r"(cnt) : "memory");
}
__device__ __forceinline__ void warp_arrive(uint32_t bar, uint32_t n = 1) {
  asm volatile("{.reg .pred p; elect.sync _|p, 0xffffffff; @p mbarrier.arrive.shared::cta.b64 _, [%0], %1;}" ::"r"(bar), "r"(n) : "memory");
}
__device__ __forceinline__ void mbar_expect(uint32_t bar, uint32_t bytes) {
  asm volatile("mbarrier.arrive.expect_tx.shared::cta.b64 _, [%0], %1;" ::"r"(bar), "r"(bytes) : "memory");
}
__device__ __forceinline__ void mbar_wait(uint32_t bar, uint32_t parity) {
  asm volatile("{.reg .pred p;\n"
               "LOOP:\n"
               "mbarrier.try_wait.parity.shared::cta.b64 p, [%0], %1;\n"
               "@!p bra LOOP;\n"
               "}\n" ::"r"(bar), "r"(parity) : "memory");
}
__device__ __forceinline__ void warp_tma(uint32_t dst, const CUtensorMap* map, int row, int grp, uint32_t bar) {
  asm volatile("{.reg .pred p; elect.sync _|p, 0xffffffff;\n"
               "@p mbarrier.arrive.expect_tx.shared::cta.b64 _, [%2], 16384;\n"
               "@p cp.async.bulk.tensor.3d.shared::cluster.global.mbarrier::complete_tx::bytes [%0], [%1, {%5, %3, %4}], [%2];}"
               ::"r"(dst), "l"(map), "r"(bar), "r"(row), "r"(grp), "r"(0) : "memory");
}
__device__ __forceinline__ void warp_tma_ab(uint32_t dst, const CUtensorMap* map, int row, int grp, uint32_t bar, uint32_t dsta, const void* srca) {
  asm volatile("{.reg .pred p; elect.sync _|p, 0xffffffff;\n"
               "@p mbarrier.arrive.expect_tx.shared::cta.b64 _, [%2], 24576;\n"
               "@p cp.async.bulk.shared::cluster.global.mbarrier::complete_tx::bytes [%6], [%7], 8192, [%2];\n"
               "@p cp.async.bulk.tensor.3d.shared::cluster.global.mbarrier::complete_tx::bytes [%0], [%1, {%5, %3, %4}], [%2];}"
               ::"r"(dst), "l"(map), "r"(bar), "r"(row), "r"(grp), "r"(0), "r"(dsta), "l"(srca) : "memory");
}
__device__ __forceinline__ void warp_bulk_load(uint32_t dst, const void* src, uint32_t bar) {
  asm volatile("{.reg .pred p; elect.sync _|p, 0xffffffff;\n"
               "@p mbarrier.arrive.expect_tx.shared::cta.b64 _, [%2], 8192;\n"
               "@p cp.async.bulk.shared::cluster.global.mbarrier::complete_tx::bytes [%0], [%1], 8192, [%2];}"
               ::"r"(dst), "l"(src), "r"(bar) : "memory");
}
__device__ __forceinline__ void warp_bulk_store(void* dst, uint32_t src, uint32_t bytes) {
  asm volatile("{.reg .pred p; elect.sync _|p, 0xffffffff;\n"
               "@p cp.async.bulk.global.shared::cta.bulk_group [%0], [%1], %2;\n"
               "@p cp.async.bulk.commit_group;}" ::"l"(dst), "r"(src), "r"(bytes) : "memory");
}
__device__ __forceinline__ void warp_publish(uint32_t* flag, uint32_t v) {
  asm volatile("{.reg .pred p; elect.sync _|p, 0xffffffff;\n"
               "cp.async.bulk.wait_group 0;\n"
               "@p fence.proxy.async.global;\n"
               "@p st.release.gpu.global.u32 [%0], %1;}" ::"l"(flag), "r"(v) : "memory");
}
__device__ __forceinline__ void bulk_load(uint32_t dst, const void* src, uint32_t bytes, uint32_t bar) {
  asm volatile("cp.async.bulk.shared::cluster.global.mbarrier::complete_tx::bytes [%0], [%1], %2, [%3];"
               ::"r"(dst), "l"(src), "r"(bytes), "r"(bar) : "memory");
}
__device__ __forceinline__ void l2_prefetch(const void* p, uint32_t bytes) {
  asm volatile("cp.async.bulk.prefetch.L2.global [%0], %1;" ::"l"(p), "r"(bytes) : "memory");
}
__device__ __forceinline__ void fence_async_smem() { asm volatile("fence.proxy.async.shared::cta;" ::: "memory"); }
__device__ __forceinline__ void fence_async_gmem() { asm volatile("fence.proxy.async.global;" ::: "memory"); }
__device__ __forceinline__ void bar_sync(int id, int n) { asm volatile("bar.sync %0, %1;" ::"r"(id), "r"(n) : "memory"); }
__device__ __forceinline__ void st_flag(uint32_t* p, uint32_t v) {
  asm volatile("st.relaxed.gpu.global.u32 [%0], %1;" ::"l"(p), "r"(v) : "memory");
}
__device__ __forceinline__ uint32_t ld_flag(const uint32_t* p) {
  uint32_t v;
  asm volatile("ld.relaxed.gpu.global.u32 %0, [%1];" : "=r"(v) : "l"(p) : "memory");
  return v;
}
__device__ __forceinline__ void poll_flag(const uint32_t* p, uint32_t want) {
  for (uint32_t n = 0; ld_flag(p) != want; n++)
    if (n > 4000000u) __trap();
  uint32_t v;
  asm volatile("ld.acquire.gpu.global.u32 %0, [%1];" : "=r"(v) : "l"(p) : "memory");
}
template <int N> __device__ __forceinline__ void zero_words(uint4* p) {
#pragma unroll
  for (int i = 0; i < N; i++) asm volatile("st.global.v4.u32 [%0], {%1,%1,%1,%1};" ::"l"(p + i * 32), "r"(0) : "memory");
}
template <int N> __device__ __forceinline__ bool has_zero_word(uint32_t addr, int stride) {
  bool bad = false;
#pragma unroll
  for (int i = 0; i < N; i++) {
    uint32_t v0, v1, v2, v3;
    asm volatile("ld.shared.v4.u32 {%0,%1,%2,%3}, [%4];" : "=r"(v0), "=r"(v1), "=r"(v2), "=r"(v3) : "r"(addr + i * stride) : "memory");
    bad |= (v0 | v1 | v2 | v3) == 0;
  }
  return bad;
}
__device__ __forceinline__ bool quarter_suspect(uint32_t addr, int lane) {
  uint32_t a0, a1, b0, b1;
  addr += lane * 32 + ((lane >> 2) & 3) * 8;
  asm volatile("ld.shared.v2.u32 {%0,%1}, [%2];" : "=r"(a0), "=r"(a1) : "r"(addr) : "memory");
  asm volatile("ld.shared.v2.u32 {%0,%1}, [%2];" : "=r"(b0), "=r"(b1) : "r"(addr + 1024) : "memory");
  return __any_sync(0xffffffffu, (a0 | a1) == 0 || (b0 | b1) == 0);
}
__device__ __forceinline__ void stsm_x4(uint32_t addr, uint32_t r0, uint32_t r1, uint32_t r2, uint32_t r3) {
  asm volatile("stmatrix.sync.aligned.m8n8.x4.shared.b16 [%0], {%1,%2,%3,%4};" ::"r"(addr), "r"(r0), "r"(r1), "r"(r2), "r"(r3) : "memory");
}
__device__ __forceinline__ void sts128(uint32_t addr, uint32_t r0, uint32_t r1, uint32_t r2, uint32_t r3) {
  asm volatile("st.shared.v4.u32 [%0], {%1,%2,%3,%4};" ::"r"(addr), "r"(r0), "r"(r1), "r"(r2), "r"(r3) : "memory");
}
__device__ __forceinline__ int fresh_tid() { int v; asm volatile("mov.u32 %0, %%tid.x;" : "=r"(v)); return v; }
__device__ __forceinline__ bool any_of4(uint32_t addr) {
  uint32_t a, b, c, d;
  asm volatile("ld.shared.v4.u32 {%0,%1,%2,%3}, [%4];" : "=r"(a), "=r"(b), "=r"(c), "=r"(d) : "r"(addr) : "memory");
  return __shfl_sync(0xffffffffu, a | b | c | d, 0) != 0;
}
__device__ __forceinline__ float ex2(float x) { float y; asm("ex2.approx.ftz.f32 %0, %1;" : "=f"(y) : "f"(x)); return y; }
__device__ __forceinline__ float rcp(float x) { float y; asm("rcp.approx.ftz.f32 %0, %1;" : "=f"(y) : "f"(x)); return y; }
__device__ __forceinline__ uint32_t pack_bf16(float lo, float hi) {
  uint32_t y; asm("cvt.rn.bf16x2.f32 %0, %1, %2;" : "=r"(y) : "f"(hi), "f"(lo)); return y;
}
__device__ __forceinline__ float bf_lo(uint32_t v) { return __uint_as_float(v << 16); }
__device__ __forceinline__ float bf_hi(uint32_t v) { return __uint_as_float(v & 0xFFFF0000u); }
__device__ __forceinline__ uint32_t hfma2bf(uint32_t a, uint32_t b, uint32_t c) {
  uint32_t d; asm("fma.rn.bf16x2 %0, %1, %2, %3;" : "=r"(d) : "r"(a), "r"(b), "r"(c)); return d;
}
__device__ __forceinline__ uint32_t exp2_pair_fma(float a, float b) {
  const float M = 98304.f + 127.f;
  uint32_t x = __byte_perm(__float_as_uint(a + M), __float_as_uint(b + M), 0x5410);
  uint32_t y, r;
  asm("lop3.b32 %0, %1, 0x007F007F, %2, 0xEA;" : "=r"(y) : "r"(x), "r"(0x3F803F80u));
  const uint32_t h = hfma2bf(y, hfma2bf(y, 0x3EAF3EAFu, 0xBD09BD09u), 0x3F323F32u);
  asm("lop3.b32 %0, %1, 0x007F007F, %2, 0xB8;" : "=r"(r) : "r"(x), "r"(h));
  return r;
}

template <int PEND, bool NEXT>
__device__ __forceinline__ void attn_step(float (&s)[32], uint32_t (&p)[16], float (&o)[12], uint64_t dv, const uint32_t (&qn)[4], uint64_t dkn) {
  if (PEND >= 0) WG_WAIT(PEND < 0 ? 0 : PEND);
  fence_regs(s);
#pragma unroll
  for (int c = 0; c < 4; c++) {
#pragma unroll
    for (int i = 4 * c; i < 4 * c + 4; i++)
      p[i] = ((POLY_MASK >> i) & 1) ? exp2_pair_fma(s[2 * i], s[2 * i + 1]) : pack_bf16(ex2(s[2 * i]), ex2(s[2 * i + 1]));
    if (c != 2) {
      const int c0 = c == 3 ? 2 : c;
#pragma unroll
      for (int i = 4 * c0; i < 4 * c + 4; i++) asm volatile("" : "+r"(p[i])::"memory");
      WG_FENCE();
      if (c == 3 && NEXT) { wgmma_rs_n64(s, qn[0], qn[1], qn[2], qn[3], dkn, 0); WG_COMMIT(); }
#pragma unroll
      for (int k = c0; k <= c; k++) wgmma_rs_n24_tb(o, p[4 * k], p[4 * k + 1], p[4 * k + 2], p[4 * k + 3], dv + k * 16, 1);
      WG_COMMIT();
    }
  }
}

template <int NC>
__device__ __forceinline__ void mish_store(const float (&acc)[64], float ratio0, float ratio1, uint32_t b1a, uint32_t sta, uint32_t stx,
                                           const uint32_t* breg = nullptr) {
#pragma unroll
  for (int c = 0; c < NC; c += 2) {
    uint32_t r[4];
#pragma unroll
    for (int u = 0; u < 2; u++) {
      float b0, b1, a[4];
      if (breg) { b0 = bf_lo(breg[c + u]); b1 = bf_hi(breg[c + u]); }
      else asm volatile("ld.shared.v2.f32 {%0,%1}, [%2];" : "=f"(b0), "=f"(b1) : "r"(b1a + (c + u) * 32));
#pragma unroll
      for (int e = 0; e < 4; e++) {
        const float h = fmaf(acc[4 * (c + u) + e], (e & 2) ? ratio1 : ratio0, (e & 1) ? b1 : b0);
        const float w = fmaf(ex2(h * 1.4426950408889634f), 0.7071067811865476f, 0.7071067811865476f);
        a[e] = fmaf(-h, rcp(fmaf(w, w, 0.5f)), h);
      }
      r[2 * u] = pack_bf16(a[0], a[1]); r[2 * u + 1] = pack_bf16(a[2], a[3]);
    }
    stsm_x4(sta + (c >> 3) * 8192 + (stx ^ ((c & 7) << 4)), r[0], r[1], r[2], r[3]);
  }
}

struct Params {
  const __nv_bfloat16 *x, *wq, *wk, *wv, *b1, *w1, *w2, *wo;
  __nv_bfloat16* out;
};

#define GEMM_CHUNK(GDEPTH, WGMMA, ACC, DA, DB, FIRST, REL_PREV)                              \
  do {                                                                                       \
    const uint64_t da_ = (DA), db_ = (DB);                                                   \
    WG_FENCE();                                                                              \
    _Pragma("unroll") for (int kk = 0; kk < 4; kk++) {                                       \
      WGMMA(ACC, da_ + kk * 2, db_ + kk * 128, !((FIRST) && kk == 0));                       \
      if (GDEPTH == 1) { WG_COMMIT(); WG_WAIT(0); if (kk == 0) { REL_PREV; } }               \
      if (GDEPTH == 2) { WG_COMMIT(); WG_WAIT(1); if (kk == 0) { REL_PREV; } }               \
    }                                                                                        \
    if (GDEPTH == 4) { WG_COMMIT(); WG_WAIT(1); REL_PREV; }                                  \
  } while (0)

template <bool HELP>
__global__ void __launch_bounds__(512, 1)
fused_kernel(const Params prm, const __grid_constant__ CUtensorMap map_wq, const __grid_constant__ CUtensorMap map_w1,
             const __grid_constant__ CUtensorMap map_w1t, const __grid_constant__ CUtensorMap map_w2,
             const __grid_constant__ CUtensorMap map_wo) {
  extern __shared__ uint8_t smem_raw[];
  constexpr uint32_t sb = 1024, bars = sb + OFF_BAR;
  const int tid = threadIdx.x, lane = tid & 31, warp = __shfl_sync(0xffffffffu, tid >> 5, 0);
  const int rb = blockIdx.x >> 2, j = blockIdx.x & 3;

  auto init_barriers = [&]() {
#pragma unroll
    for (uint32_t i = 0; i < B_COUNT; i++) mbar_init(bars + 8 * i, i < B_BEMPTY || i == B_EPOCH ? 1 : i <= B_QDONE ? 8 : 4);
    asm volatile("fence.mbarrier_init.release.cluster;" ::: "memory");
    mbar_expect(bars + 8 * B_EPOCH, 16);
    bulk_load(sb + OFF_MISC, &g_epoch, 16, bars + 8 * B_EPOCH);
  };
  auto get_epoch = [&]() {
    uint32_t e;
    mbar_wait(bars + 8 * B_EPOCH, 0);
    asm volatile("ld.shared.u32 %0, [%1];" : "=r"(e) : "r"(sb + OFF_MISC) : "memory");
    return e + 1;
  };
  constexpr int NOWN = HELP ? 6 : 7;
  constexpr uint32_t PH = HELP ? 1 : 0;

  if (__builtin_expect(HELP && blockIdx.x >= NCTA, 0)) {
    const int jp = blockIdx.x & 1, rb0 = ((blockIdx.x >> 1) & 1) * 16, hw = warp >> 2, wq = warp & 3;
    constexpr uint32_t OFF_HST = OFF_KV + 8192, OFF_HRA = OFF_HST + 32768;
    static_assert(OFF_HRA + 512 <= OFF_BAR, "helper smem");
    if (tid == 0) init_barriers();
    __syncthreads();
    if (hw < 2) {
      asm volatile("setmaxnreg.dec.sync.aligned.u32 40;");
      const uint32_t epoch = get_epoch();
      if (warp == 0) {
#pragma unroll 1
        for (int c = 0; c < 8; c++) warp_tma(sb + OFF_BR + c * 16384, &map_w1t, 128 * (c & 3), 7 * (2 * jp + (c >> 2)) + 6, bars + 8 * c);
        poll_flag(g_s.xnflag + (rb0 * 4 + lane) * 8, epoch);
        poll_flag(g_s.xnflag + (rb0 * 4 + 32 + lane) * 8, epoch);
        fence_async_gmem();
        __syncwarp();
#pragma unroll 1
        for (int b = 0; b < 16; b++) {
#pragma unroll 1
          for (int p = 0; p < 4; p++) {
            if (b > 0) mbar_wait(bars + 8 * B_ACTT + 8 * p, (b - 1) & 1);
            asm volatile("{.reg .pred p; elect.sync _|p, 0xffffffff;\n"
                         "@p mbarrier.arrive.expect_tx.shared::cta.b64 _, [%2], 16448;\n"
                         "@p cp.async.bulk.shared::cluster.global.mbarrier::complete_tx::bytes [%0], [%1], 16384, [%2];\n"
                         "@p cp.async.bulk.shared::cluster.global.mbarrier::complete_tx::bytes [%3], [%4], 64, [%2];}"
                         ::"r"(sb + OFF_XA + p * 16384), "l"(g_s.xn + ((rb0 + b) * 8 + 2 * p) * 512), "r"(bars + 8 * B_HFULL + 8 * p + 32 * (b & 1)),
                           "r"(sb + OFF_HRA + (b & 1) * 256 + p * 64), "l"(g_s.ratio + (rb0 + b) * 16 + p * 4) : "memory");
          }
        }
      } else if (warp < 3) {
        const int w = warp - 1;
#pragma unroll 1
        for (int b = w; b < 16; b += 2) {
          mbar_wait(bars + 8 * B_OOWN + 8 * w, (b >> 1) & 1);
          warp_bulk_store(g_s.ex + (((rb0 + b) * 4 + 2 * jp) * 11 + 6) * 512, sb + OFF_HST + w * 16384, 8192);
          warp_bulk_store(g_s.ex + (((rb0 + b) * 4 + 2 * jp + 1) * 11 + 6) * 512, sb + OFF_HST + w * 16384 + 8192, 8192);
          warp_publish(g_s.hflag + ((rb0 + b) * 2 + jp) * 8, epoch);
          warp_arrive(bars + 8 * B_LAST + 8 * w, 4);
        }
      }
    } else {
      asm volatile("setmaxnreg.inc.sync.aligned.u32 208;");
      const int w = hw & 1, g = lane >> 2;
      const uint32_t st_row = wq * 16 + (lane & 7) + ((lane >> 3) & 1) * 8;
      constexpr uint64_t da = desc_a(sb + OFF_XA), db = mkdesc(sb + OFF_BR, 65536, 1024, 1);
      float acc[64];
      uint32_t breg[16];
#pragma unroll
      for (int i = 0; i < 64; i++) acc[i] = 0.f;
#pragma unroll
      for (int c = 0; c < 16; c++)
        breg[c] = __ldg(reinterpret_cast<const uint32_t*>(prm.b1 + 448 * (2 * jp + (c >> 3)) + 384 + (c & 7) * 8) + (lane & 3));
#pragma unroll 1
      for (int c = 0; c < 8; c++) mbar_wait(bars + 8 * c, 0);
#pragma unroll 1
      for (int b = w; b < 16; b += 2) {
        fence_regs(acc);
        float ratio0 = 0.f, ratio1 = 0.f;
#pragma unroll
        for (int p = 0; p < 4; p++) {
          mbar_wait(bars + 8 * (B_HFULL + p) + 32 * w, (b >> 1) & 1);
          if (p == wq) {
            asm volatile("ld.shared.f32 %0, [%1];" : "=f"(ratio0) : "r"(sb + OFF_HRA + w * 256 + (wq * 16 + g) * 4) : "memory");
            asm volatile("ld.shared.f32 %0, [%1];" : "=f"(ratio1) : "r"(sb + OFF_HRA + w * 256 + (wq * 16 + g + 8) * 4) : "memory");
          }
          WG_FENCE();
#pragma unroll
          for (int kk = 0; kk < 8; kk++)
            wgmma_ss_n128_tb(acc, da + p * 1024 + (kk >> 2) * 512 + (kk & 3) * 2, db + p * 1024 + kk * 128, p + kk > 0);
          WG_COMMIT(); WG_WAIT(1);
          if (p > 0) warp_arrive(bars + 8 * B_ACTT + 8 * (p - 1));
        }
        WG_WAIT(0);
        fence_regs(acc);
        warp_arrive(bars + 8 * B_ACTT + 24);
        mbar_wait(bars + 8 * B_LAST + 8 * w, ((b >> 1) & 1) ^ 1);
        mish_store<16>(acc, ratio0, ratio1, 0, sb + OFF_HST + w * 16384 + st_row * 128, ((lane >> 4) ^ (st_row & 7)) << 4, breg);
        fence_async_smem();
        __syncwarp();
        warp_arrive(bars + 8 * B_OOWN + 8 * w);
      }
    }
    return;
  }

  if (warp == 0) {
    if ((uint32_t)__cvta_generic_to_shared(smem_raw) > sb) __trap();
    if (lane == 0) {
      l2_prefetch(reinterpret_cast<const uint8_t*>(prm.wq) + blockIdx.x * 4096, 4096);
      init_barriers();
    }
    __syncwarp();
    asm volatile("bar.arrive 0, 512;" ::: "memory");
    bar_sync(4, 512);
#pragma unroll 1
    for (int c = 0; c < 8; c++) warp_tma(sb + OFF_BR + c * 16384, &map_wq, 64 * c, 2 * j, bars + 8 * c);
  } else {
    const int row4 = warp * 4, row5 = warp == 13 ? 3 : (warp >> 2) - 1;
    uint4 v[5][2];
    const uint4* xr = reinterpret_cast<const uint4*>(prm.x + (size_t)(rb * 64) * D_) + lane;
    const bool five = (warp & 3) == 0 || warp == 13;
#pragma unroll
    for (int r = 0; r < 4; r++) { v[r][0] = __ldg(xr + (row4 + r) * 64); v[r][1] = __ldg(xr + (row4 + r) * 64 + 32); }
    v[4][0] = v[4][1] = make_uint4(0, 0, 0, 0);
    if (five) { v[4][0] = __ldg(xr + row5 * 64); v[4][1] = __ldg(xr + row5 * 64 + 32); }
    const __nv_bfloat16* wsrc = (j < 2 ? prm.wk : prm.wv) + (j & 1) * 8;
    const uint4 wkv = __ldg(reinterpret_cast<const uint4*>(wsrc + tid * 16));
    uint4 wkv0 = make_uint4(0, 0, 0, 0);
    if (warp == 15) wkv0 = __ldg(reinterpret_cast<const uint4*>(wsrc + lane * 16));
    float b1v = 0.f;
    if (tid >= 64) b1v = __bfloat162float(prm.b1[448 * j + tid - 64]);
    if (tid >= 128) {
      const int t = tid - 128;
      sts128(sb + OFF_KV + (t >> 7) * KV_SLOT + 8192 + (t & 127) * 16, 0x3F803F80u, 0x3F803F80u, 0x3F803F80u, 0x3F803F80u);
    }
    float mu[5], rs[5];
#pragma unroll
    for (int r = 0; r < 5; r++) {
      mu[r] = rs[r] = 0.f;
      if (r < 4 || five) {
        const uint32_t w[8] = {v[r][0].x, v[r][0].y, v[r][0].z, v[r][0].w, v[r][1].x, v[r][1].y, v[r][1].z, v[r][1].w};
#pragma unroll
        for (int i = 0; i < 8; i++) {
          const float lo = bf_lo(w[i]), hi = bf_hi(w[i]);
          mu[r] += lo; rs[r] = fmaf(lo, lo, rs[r]);
          mu[r] += hi; rs[r] = fmaf(hi, hi, rs[r]);
        }
      }
    }
    asm volatile("bar.arrive 4, 512;" ::"f"(mu[0]), "f"(mu[1]), "f"(mu[2]), "f"(mu[3]), "f"(mu[4]) : "memory");
    auto row_consts = [&](float u, int row, bool wr) {
      const float o = __shfl_xor_sync(0xffffffffu, u, 16);
      const float m = ((lane & 16) ? o : u) * (1.f / D_), q = ((lane & 16) ? u : o) * (1.f / D_);
      float k;
      asm("rsqrt.approx.ftz.f32 %0, %1;" : "=f"(k) : "f"(fmaxf(fmaf(-m, m, q), 0.f) + 1e-5f));
      const float kh = bf_lo(pack_bf16(k, k));
      if (wr) asm volatile("st.shared.f32 [%0], %1;" ::"r"(sb + OFF_RATIO + row * 4), "f"(k * rcp(kh)) : "memory");
      return pack_bf16(kh, -m * kh);
    };
    auto row_store = [&](const uint4 (&vr)[2], uint32_t kc, int row) {
      uint32_t khi, c;
      asm("{.reg .b16 l, h; mov.b32 {l, h}, %2; mov.b32 %0, {l, l}; mov.b32 %1, {h, h};}" : "=r"(khi), "=r"(c) : "r"(kc));
#pragma unroll
      for (int h = 0; h < 2; h++)
        sts128(sb + OFF_XA + (h * 4 + (lane >> 3)) * 8192 + row * 128 + (((lane & 7) ^ (row & 7)) << 4),
               hfma2bf(vr[h].x, khi, c), hfma2bf(vr[h].y, khi, c), hfma2bf(vr[h].z, khi, c), hfma2bf(vr[h].w, khi, c));
    };
    {
      float a[4];
#pragma unroll
      for (int r = 0; r < 4; r++) a[r] = ((lane & 16) ? rs[r] : mu[r]) + __shfl_xor_sync(0xffffffffu, (lane & 16) ? mu[r] : rs[r], 16);
#pragma unroll
      for (int r = 0; r < 2; r++) a[r] = ((lane & 8) ? a[2 + r] : a[r]) + __shfl_xor_sync(0xffffffffu, (lane & 8) ? a[r] : a[2 + r], 8);
      float u = ((lane & 4) ? a[1] : a[0]) + __shfl_xor_sync(0xffffffffu, (lane & 4) ? a[0] : a[1], 4);
      u += __shfl_xor_sync(0xffffffffu, u, 2);
      u += __shfl_xor_sync(0xffffffffu, u, 1);
      const uint32_t kc = row_consts(u, row4 + ((lane >> 2) & 3), (lane & 19) == 0);
#pragma unroll
      for (int r = 0; r < 4; r++) row_store(v[r], __shfl_sync(0xffffffffu, kc, 4 * r), row4 + r);
    }
    if (five) {
      float u = ((lane & 16) ? rs[4] : mu[4]) + __shfl_xor_sync(0xffffffffu, (lane & 16) ? mu[4] : rs[4], 16);
#pragma unroll
      for (int o = 8; o; o >>= 1) u += __shfl_xor_sync(0xffffffffu, u, o);
      row_store(v[4], row_consts(u, row5, lane == 0), row5);
    }
    sts128(sb + OFF_WKV + tid * 16, wkv.x, wkv.y, wkv.z, wkv.w);
    if (warp == 15) sts128(sb + OFF_WKV + lane * 16, wkv0.x, wkv0.y, wkv0.z, wkv0.w);
    if (tid >= 64) asm volatile("st.shared.f32 [%0], %1;" ::"r"(sb + OFF_B1 + (tid - 64) * 4), "f"(b1v) : "memory");
    fence_async_smem();
    bar_sync(0, 512);
  }
  const int wg = warp >> 2, wq = warp & 3;

  if (wg >= 2) {
    asm volatile("setmaxnreg.inc.sync.aligned.u32 %0;" ::"n"(REG_ATT));
    int tid = fresh_tid(), lane = tid & 31;
    const int w = wg - 2;
    float sx[32], sy[32], o[4][12];
    uint32_t q[4][4], pa[16], pb[16];
#pragma unroll
    for (int i = 0; i < 32; i++) { sx[i] = 0.f; sy[i] = 0.f; }
    if (w == 0) {
      float sq[64];
#pragma unroll
      for (int i = 0; i < 64; i++) sq[i] = 0.f;
      float sc0, sc1;
      asm volatile("ld.shared.f32 %0, [%1];" : "=f"(sc0) : "r"(sb + OFF_RATIO + (wq * 16 + (lane >> 2)) * 4));
      asm volatile("ld.shared.f32 %0, [%1];" : "=f"(sc1) : "r"(sb + OFF_RATIO + (wq * 16 + (lane >> 2) + 8) * 4));
      sc0 *= 0.25f * 1.4426950408889634f; sc1 *= 0.25f * 1.4426950408889634f;
      mbar_wait(bars + 8 * B_KVMMA, 0);
      fence_regs(sq);
      constexpr uint64_t da = desc_a(sb + OFF_XA), db = desc_b(sb + OFF_BR);
#pragma unroll 1
      for (int c = 0; c < 8; c++) {
        mbar_wait(bars + 8 * c, 0);
        WG_FENCE();
#pragma unroll
        for (int kk = 0; kk < 4; kk++) wgmma_ss_n128_tb(sq, da + c * 512 + kk * 2, db + c * 1024 + kk * 128, 1);
        WG_COMMIT(); WG_WAIT(1);
        if (c > 0 && c <= 4) warp_arrive(bars + 8 * B_BEMPTY + 8 * (c - 1), 2);
      }
      WG_WAIT(0);
      fence_regs(sq);
      warp_arrive(bars + 8 * B_QDONE, 2);
#pragma unroll
      for (int t = 0; t < 4; t++)
        sts128(sb + OFF_WKV + t * 2048 + (tid & 127) * 16, pack_bf16(sq[32 + 8 * t] * sc0, sq[33 + 8 * t] * sc0),
               pack_bf16(sq[34 + 8 * t] * sc1, sq[35 + 8 * t] * sc1), pack_bf16(sq[36 + 8 * t] * sc0, sq[37 + 8 * t] * sc0),
               pack_bf16(sq[38 + 8 * t] * sc1, sq[39 + 8 * t] * sc1));
      asm volatile("bar.arrive 6, 256;" ::: "memory");
#pragma unroll
      for (int t = 0; t < 4; t++)
#pragma unroll
        for (int i = 0; i < 4; i++) {
          const float sc = (i & 1) ? sc1 : sc0;
          q[t][i] = pack_bf16(sq[8 * t + 2 * i] * sc, sq[8 * t + 2 * i + 1] * sc);
        }
    } else {
      mbar_wait(bars + 8 * (B_KVFULL + 1), 0);
      bool bad = quarter_suspect(sb + OFF_KV + KV_SLOT + wq * 2048, lane);
      mbar_wait(bars + 8 * (B_KVFULL + 2), 0);
      bad |= quarter_suspect(sb + OFF_KV + 2 * KV_SLOT + wq * 2048, lane);
      if (lane == 0) asm volatile("st.shared.u32 [%0], %1;" ::"r"(sb + OFF_MISC + 48 + wq * 4), "r"((uint32_t)bad) : "memory");
      __syncwarp();
      warp_arrive(bars + 8 * B_KVCHK);
      bar_sync(6, 256);
#pragma unroll
      for (int t = 0; t < 4; t++)
        asm volatile("ld.shared.v4.u32 {%0,%1,%2,%3}, [%4];" : "=r"(q[t][0]), "=r"(q[t][1]), "=r"(q[t][2]), "=r"(q[t][3])
                     : "r"(sb + OFF_WKV + t * 2048 + (tid & 127) * 16) : "memory");
    }
    float qmax = 0.f;
#pragma unroll
    for (int t = 0; t < 4; t++) {
      float n0 = 0.f, n1 = 0.f;
#pragma unroll
      for (int i = 0; i < 4; i++) {
        const float n = bf_lo(q[t][i]) * bf_lo(q[t][i]) + bf_hi(q[t][i]) * bf_hi(q[t][i]);
        if (i & 1) n1 += n; else n0 += n;
      }
      n0 += __shfl_xor_sync(0xffffffffu, n0, 1); n1 += __shfl_xor_sync(0xffffffffu, n1, 1);
      n0 += __shfl_xor_sync(0xffffffffu, n0, 2); n1 += __shfl_xor_sync(0xffffffffu, n1, 2);
      asm("max.NaN.f32 %0, %1, %2;" : "=f"(n0) : "f"(n0), "f"(n1));
      asm("max.NaN.f32 %0, %1, %2;" : "=f"(qmax) : "f"(qmax), "f"(n0));
#pragma unroll
      for (int i = 0; i < 12; i++) o[t][i] = 0.f;
    }
    mbar_wait(bars + 8 * B_KMAX, 0);
    uint32_t safe;
    {
      float kmax;
      asm volatile("ld.shared.f32 %0, [%1];" : "=f"(kmax) : "r"(sb + OFF_MISC + 32) : "memory");
      const uint32_t ok = (qmax * kmax <= 3600.f) ? 1u : 0u;
      asm volatile("{.reg .pred p, r; setp.ne.u32 p, %1, 0; bar.red.and.pred r, %2, 128, p; selp.u32 %0, 1, 0, r;}"
                   : "=r"(safe) : "r"(ok), "r"(2 + w) : "memory");
      safe = __shfl_sync(0xffffffffu, safe, 0);
    }
    const uint64_t dk0 = mkdesc(sb + OFF_KV, 2048, 128, 0), dv0 = mkdesc(sb + OFF_KV + 4096, 128, 2048, 0);
#pragma unroll
    for (int t = 0; t < 4; t++) { fence_regs(o[t]); fence_regs(q[t]); }
    fence_regs(sx); fence_regs(sy);
#define QK(S, T, DK) wgmma_rs_n64(S, q[T][0], q[T][1], q[T][2], q[T][3], DK, 0)
    if (__builtin_expect(safe, 1)) {
      uint32_t slot = 1, prev = 0, par = 0;
      if (SKEW && w == 1) mbar_wait(bars + 8 * B_SKEW, 0);
      for (int it = 0; it < 16; it++) {
        mbar_wait(bars + 8 * B_KVFULL + 8 * slot, par);
        const uint64_t dk = dk0 + slot * (KV_SLOT >> 4), dv = dv0 + slot * (KV_SLOT >> 4);
        WG_FENCE();
        QK(sx, 0, dk); WG_COMMIT();
        QK(sy, 1, dk); WG_COMMIT();
        WG_WAIT(1);
        if (it > 0) warp_arrive(bars + 8 * B_KVEMPTY + 8 * prev);
#pragma unroll
        for (int s = 0; s < 8; s += 2) {
          if (SKEW && s == (SKEW & 7) && it == (SKEW >> 3) && w == 0) warp_arrive(bars + 8 * B_SKEW);
          if (s == 0) attn_step<-1, true>(sx, pa, o[0], dv, q[2], dk);
          else if (s < 6) attn_step<4, true>(sx, pa, o[s & 3], dv + (s >> 2) * 64, q[(s + 2) & 3], dk + ((s + 2) >> 2) * 64);
          else attn_step<4, false>(sx, pa, o[2], dv + 64, q[0], dk);
          if (s < 6) attn_step<4, true>(sy, pb, o[(s + 1) & 3], dv + (s >> 2) * 64, q[(s + 3) & 3], dk + ((s + 3) >> 2) * 64);
          else attn_step<3, false>(sy, pb, o[3], dv + 64, q[0], dk);
        }
        prev = slot;
        if (++slot == 3) slot = 0;
        if (slot == 1) par ^= 1;
      }
      WG_WAIT(0);
      warp_arrive(bars + 8 * (B_KVEMPTY + 1));
    } else if (SKEW && w == 0) {
      warp_arrive(bars + 8 * B_SKEW);
    }
    mbar_wait(bars + 8 * B_KVCHK, 0);
    uint32_t slot = safe ? 2 : 1, par = safe;
    int pass = (safe ? 0 : 1) + (any_of4(sb + OFF_MISC + 48) ? 1 : 0);
#pragma unroll 1
    for (; __builtin_expect(pass > 0, 0); pass--) {
      float m[4][2];
#pragma unroll
      for (int t = 0; t < 4; t++) {
        m[t][0] = m[t][1] = -INFINITY;
#pragma unroll
        for (int i = 0; i < 12; i++) o[t][i] = 0.f;
        fence_regs(o[t]);
      }
      for (int it = 0; it < 16; it++) {
        mbar_wait(bars + 8 * B_KVFULL + 8 * slot, par);
        for (int h = 0; h < 2; h++) {
          const uint64_t dk = dk0 + slot * (KV_SLOT >> 4) + h * 64, dv = dv0 + slot * (KV_SLOT >> 4) + h * 64;
#pragma unroll
          for (int t = 0; t < 4; t++) {
            WG_FENCE();
            QK(sx, t, dk); WG_COMMIT(); WG_WAIT(0);
            fence_regs(sx);
            float m0 = m[t][0], m1 = m[t][1];
#pragma unroll
            for (int i = 0; i < 8; i++) {
              m0 = fmaxf(m0, fmaxf(sx[4 * i], sx[4 * i + 1]));
              m1 = fmaxf(m1, fmaxf(sx[4 * i + 2], sx[4 * i + 3]));
            }
            m0 = fmaxf(m0, __shfl_xor_sync(0xffffffffu, m0, 1)); m1 = fmaxf(m1, __shfl_xor_sync(0xffffffffu, m1, 1));
            m0 = fmaxf(m0, __shfl_xor_sync(0xffffffffu, m0, 2)); m1 = fmaxf(m1, __shfl_xor_sync(0xffffffffu, m1, 2));
            const float a0 = ex2(m[t][0] - m0), a1 = ex2(m[t][1] - m1);
            m[t][0] = m0; m[t][1] = m1;
#pragma unroll
            for (int i = 0; i < 12; i++) o[t][i] *= (i & 2) ? a1 : a0;
#pragma unroll
            for (int i = 0; i < 16; i++) {
              const float mm = (i & 1) ? m1 : m0;
              pa[i] = pack_bf16(ex2(sx[2 * i] - mm), ex2(sx[2 * i + 1] - mm));
            }
            fence_regs(pa); fence_regs(o[t]);
            WG_FENCE();
#pragma unroll
            for (int c = 0; c < 4; c++) wgmma_rs_n24_tb(o[t], pa[4 * c], pa[4 * c + 1], pa[4 * c + 2], pa[4 * c + 3], dv + c * 16, 1);
            WG_COMMIT(); WG_WAIT(0);
            fence_regs(o[t]);
          }
        }
        warp_arrive(bars + 8 * B_KVEMPTY + 8 * slot);
        if (++slot == 3) slot = 0;
        if (slot == 1) par ^= 1;
      }
    }
#pragma unroll
    for (int t = 0; t < 4; t++) fence_regs(o[t]);
    tid = fresh_tid(); lane = tid & 31;
    const uint32_t epoch = __shfl_sync(0xffffffffu, get_epoch(), 0);
    mbar_wait(bars + 8 * (B_ACTT + (HELP ? 2 : 3)), 0);
    const uint32_t st_row = wq * 16 + (lane & 7) + ((lane >> 3) & 1) * 8;
#pragma unroll
    for (int t = 0; t < 4; t++) {
      const float r0 = rcp(o[t][8]), r1 = rcp(o[t][10]);
      const uint32_t unit = 2 * t + (lane >> 4);
      stsm_x4(sb + OFF_XA + (4 + w) * 8192 + st_row * 128 + ((unit ^ (st_row & 7)) << 4),
              pack_bf16(o[t][0] * r0, o[t][1] * r0), pack_bf16(o[t][2] * r1, o[t][3] * r1),
              pack_bf16(o[t][4] * r0, o[t][5] * r0), pack_bf16(o[t][6] * r1, o[t][7] * r1));
    }
    fence_async_smem();
    __syncwarp();
    warp_arrive(bars + 8 * B_OOWN + 8 * w);
    warp_bulk_store(g_s.ex + (blockIdx.x * 11 + 7 + 2 * (epoch & 1) + w) * 512 + wq * 128, sb + OFF_XA + (4 + w) * 8192 + wq * 2048, 2048);
    asm volatile("cp.async.bulk.wait_group 0;" ::: "memory");
    bar_sync(2 + w, 128);
    if (wq == 0) {
      if (lane == 0) st_flag(g_oflag + (blockIdx.x * 2 + w) * 8, epoch);
      __syncwarp();
      warp_arrive(bars + 8 * B_OHINT + 8 * w);
    }
    if (w == 0) {
      bool bad = false;
#pragma unroll 1
      for (int l = 0; l < 6; l++) {
        mbar_wait(bars + 8 * B_OFULL + 8 * l, 0);
        bad |= quarter_suspect(sb + OFF_ACT + l * 8192 + wq * 2048, lane);
      }
      if (lane == 0) asm volatile("st.shared.u32 [%0], %1;" ::"r"(sb + OFF_MISC + 64 + wq * 4), "r"((uint32_t)bad) : "memory");
      __syncwarp();
      warp_arrive(bars + 8 * B_OCHK);
      mbar_wait(bars + 8 * B_OCHK, 0);
      if (__builtin_expect(any_of4(sb + OFF_MISC + 64), 0)) {
        mbar_wait(bars + 8 * B_OMMA, 0);
#pragma unroll 1
        for (int l = 0; l < 6; l++) {
          const int sw = l >= 3, src = rb * 4 + ((j + 1 + l - 3 * sw) & 3);
          poll_flag(g_s.oflag2 + (src * 2 + sw) * 8, epoch);
#pragma unroll 1
          for (int i = tid & 127; i < 512; i += 128) {
            const uint32_t a = sb + OFF_ACT + l * 8192 + i * 16;
            uint32_t v0 = 0, v1 = 0, v2 = 0, v3 = 0;
            if (has_zero_word<1>(a, 0))
              asm volatile("ld.relaxed.gpu.global.v4.u32 {%0,%1,%2,%3}, [%4];" : "=r"(v0), "=r"(v1), "=r"(v2), "=r"(v3)
                           : "l"(g_s.ex + (src * 11 + 7 + 2 * (epoch & 1) + sw) * 512 + i) : "memory");
            sts128(a, v0, v1, v2, v3);
          }
        }
        fence_async_smem();
        __syncwarp();
        warp_arrive(bars + 8 * B_OFIX);
      }
    }
  } else if (wg == 0) {
    asm volatile("setmaxnreg.dec.sync.aligned.u32 %0;" ::"n"(REG_PROD));
    if (warp == 0 || warp == 3) {
      const int odd = warp & 1;
      uint32_t st = odd;
#define RING_WAIT() mbar_wait(bars + 8 * B_BEMPTY + 8 * (st & 3), (st >> 2) & 1)
#define RING(MAP, ROW, GRP) do { RING_WAIT(); warp_tma(sb + OFF_BR + (st & 3) * 16384, MAP, ROW, GRP, bars + 8 * B_BFULL + 8 * (st & 3)); st += 2; } while (0)
#pragma unroll 1
      for (int i = odd; i < 24; i += 2) RING(&map_w1, 64 * (i & 7), 7 * j + 2 * (i >> 3));
      if (!HELP) {
#pragma unroll 1
        for (int i = odd; i < 4; i += 2) RING(&map_w1t, 128 * i, 7 * j + 6);
      }
#pragma unroll 1
      for (int u = odd; u < NOWN; u += 2) RING(&map_w2, 448 * j + 64 * u, 2 * j);
      const uint32_t epoch = get_epoch();
#define RING_AB(JJ, C) do { RING_WAIT(); \
        warp_tma_ab(sb + OFF_BR + (st & 3) * 16384, &map_w2, 448 * (JJ) + 64 * (C), 2 * j, bars + 8 * B_BFULL + 8 * (st & 3), \
                    sb + OFF_XA + (st & 3) * 8192, g_s.ex + ((rb * 4 + (JJ)) * 11 + (C)) * 512); st += 2; } while (0)
      if (HELP) mbar_wait(bars + 8 * B_XNSENT, 0);
      int c = odd ^ (NOWN & 1);
#pragma unroll 1
      for (int q = 1; q < 4; q++) {
        const int jj = (j + q) & 3;
        poll_flag(g_actflag + (rb * 4 + jj) * 8, epoch);
        fence_async_gmem();
#pragma unroll 1
        for (; c < NOWN; c += 2) RING_AB(jj, c);
        c -= NOWN;
      }
      if (HELP) {
#pragma unroll 1
        for (int jp = 0; jp < 2; jp++) {
          poll_flag(g_s.hflag + (rb * 2 + jp) * 8, epoch);
          fence_async_gmem();
          RING_AB(2 * jp + odd, 6);
        }
      }
#pragma unroll 1
      for (int u = odd; u < 4; u += 2) RING(&map_wo, 128 * ((j + u) & 3), 2 * j);
      if (odd) {
        warp_tma(sb + OFF_XA, &map_wo, 128 * j + 64, 2 * j, bars + 8 * B_QFULL);
        warp_tma(sb + OFF_XA + 16384, &map_wo, 128 * ((j + 1) & 3) + 64, 2 * j, bars + 8 * (B_QFULL + 1));
      }
      mbar_wait(bars + 8 * B_BEMPTY + 8 * odd, 1 ^ PH);
      warp_tma(sb + OFF_BR + odd * 16384, &map_wo, 128 * ((j + 2 + odd) & 3) + 64, 2 * j, bars + 8 * B_BFULL + 8 * odd);
    } else if (warp == 1) {
      const uint32_t epoch = get_epoch();
      float kmax;
      for (uint32_t n = 0;; n++) {
        bool ok = true;
        kmax = 0.f;
#pragma unroll
        for (int i = 0; i < 4; i++) {
          uint32_t e, v;
          asm volatile("ld.relaxed.gpu.global.v2.u32 {%0,%1}, [%2];" : "=r"(e), "=r"(v) : "l"(g_kvflag + (lane + 32 * i) * 4) : "memory");
          ok &= e == epoch;
          const float t = __uint_as_float(v) + __shfl_down_sync(0xffffffffu, __uint_as_float(v), 1);
          if ((lane & 3) == 0) asm("max.NaN.f32 %0, %1, %2;" : "=f"(kmax) : "f"(kmax), "f"(t));
        }
        if (__all_sync(0xffffffffu, ok)) break;
        if (n > 4000000u) __trap();
      }
#pragma unroll
      for (int o = 16; o; o >>= 1) {
        const float t = __shfl_xor_sync(0xffffffffu, kmax, o);
        asm("max.NaN.f32 %0, %1, %2;" : "=f"(kmax) : "f"(kmax), "f"(t));
      }
      if (lane == 0) asm volatile("st.shared.f32 [%0], %1;" ::"r"(sb + OFF_MISC + 32), "f"(kmax) : "memory");
      __syncwarp();
      const uint4* kv = g_s.kv[epoch & 1];
      warp_bulk_load(sb + OFF_KV + KV_SLOT, kv + (rb >> 1) * 512, bars + 8 * (B_KVFULL + 1));
      warp_arrive(bars + 8 * B_KMAX);
      warp_bulk_load(sb + OFF_KV + 2 * KV_SLOT, kv + (((rb >> 1) + 1) & 15) * 512, bars + 8 * (B_KVFULL + 2));
#pragma unroll 1
      for (int i = 0; i < 4; i++) poll_flag(g_s.kvflag2 + (lane + 32 * i) * 8, epoch);
      fence_async_gmem();
      __syncwarp();
      mbar_wait(bars + 8 * B_QDONE, 0);
      warp_bulk_load(sb + OFF_KV, kv + (((rb >> 1) + 2) & 15) * 512, bars + 8 * B_KVFULL);
      mbar_wait(bars + 8 * B_KVCHK, 0);
      const int nfill = any_of4(sb + OFF_MISC + 48) ? 32 : 16;
      uint32_t slot = 1, par = 0;
#pragma unroll 1
      for (int i = 3; i < nfill; i++) {
        mbar_wait(bars + 8 * B_KVEMPTY + 8 * slot, par);
        if (i == nfill - 1) warp_arrive(bars + 8 * B_LAST, 4);
        warp_bulk_load(sb + OFF_KV + slot * KV_SLOT, kv + ((i + (rb >> 1)) & 15) * 512, bars + 8 * B_KVFULL + 8 * slot);
        if (++slot == 3) slot = 0;
        if (slot == 1) par ^= 1;
      }
#pragma unroll 1
      for (int w = 0; w < 2; w++) {
        mbar_wait(bars + 8 * B_OHINT + 8 * w, 0);
        warp_publish(g_s.oflag2 + (blockIdx.x * 2 + w) * 8, epoch);
      }
      if (blockIdx.x == 0) {
        if (HELP) poll_flag(g_s.hflag + ((lane & 2) * 16 + (lane & 1)) * 8, epoch);
        __syncwarp();
        if (lane == 0) st_flag(&g_epoch, epoch);
      }
    } else if (warp == 2) {
      const uint32_t epoch = get_epoch();
      if (lane == 0) l2_prefetch(reinterpret_cast<const uint8_t*>(prm.w1) + blockIdx.x * 14336, 14336);
      mbar_wait(bars + 8 * B_QDONE, 0);
      if (HELP) {
        mbar_wait(bars + 8 * (B_KVFULL + 2), 0);
        warp_bulk_store(g_s.xn + (rb * 8 + 2 * j) * 512, sb + OFF_XA + j * 16384, 16384);
        warp_bulk_store(g_s.ratio + rb * 16 + j * 4, sb + OFF_RATIO + j * 64, 64);
        warp_publish(g_s.xnflag + blockIdx.x * 8, epoch);
        warp_arrive(bars + 8 * B_XNSENT, 4);
      }
      if (lane == 0) {
        l2_prefetch(reinterpret_cast<const uint8_t*>(prm.w2) + blockIdx.x * 14336, 14336);
        l2_prefetch(reinterpret_cast<const uint8_t*>(prm.wo) + blockIdx.x * 4096, 4096);
      }
      __syncwarp();
#pragma unroll 1
      for (int t = 0; t < (HELP ? 3 : 4); t++) {
        mbar_wait(bars + 8 * B_ACTT + 8 * t, 0);
        warp_bulk_store(g_s.ex + (blockIdx.x * 11 + 2 * t) * 512, sb + OFF_ACT + 2 * t * 8192, t < 3 ? 16384 : 8192);
      }
      warp_publish(g_actflag + blockIdx.x * 8, epoch);
      zero_words<2>(g_s.kv[~epoch & 1] + (rb >> 1) * 512 + j * 128 + (rb & 1) * 64 + lane);
      zero_words<32>(g_s.ex + (blockIdx.x * 11 + 7 + 2 * (~epoch & 1)) * 512 + lane);
      mbar_wait(bars + 8 * B_ACTOWN, 0);
      mbar_wait(bars + 8 * B_LAST, 0);
      if (lane < 6) {
        const int sw = lane >= 3, src = rb * 4 + ((j + 1 + lane - 3 * sw) & 3);
        mbar_expect(bars + 8 * (B_OFULL + lane), 8192);
        for (uint32_t n = 0, done = 0; !done; n++) {
          if (ld_flag(g_oflag + (src * 2 + sw) * 8) == epoch) {
            bulk_load(sb + OFF_ACT + lane * 8192, g_s.ex + (src * 11 + 7 + 2 * (epoch & 1) + sw) * 512, 8192, bars + 8 * (B_OFULL + lane));
            done = 1;
          }
          if (n > 4000000u) __trap();
        }
      }
    }
  } else {
    asm volatile("setmaxnreg.dec.sync.aligned.u32 %0;" ::"n"(REG_GEMM));
    const int tid = fresh_tid(), lane = tid & 31;
    const int g = lane >> 2, t4 = lane & 3;
    float ratio0, ratio1;
    asm volatile("ld.shared.f32 %0, [%1];" : "=f"(ratio0) : "r"(sb + OFF_RATIO + (wq * 16 + g) * 4));
    asm volatile("ld.shared.f32 %0, [%1];" : "=f"(ratio1) : "r"(sb + OFF_RATIO + (wq * 16 + g + 8) * 4));
    {
      float kv[4] = {0.f, 0.f, 0.f, 0.f};
      fence_regs(kv);
      const uint64_t da = desc_a(sb + OFF_XA), db = mkdesc(sb + OFF_WKV, 128, 128, 0);
#pragma unroll 1
      for (int c = 0; c < 8; c++) {
        WG_FENCE();
#pragma unroll
        for (int kk = 0; kk < 4; kk++) wgmma_ss_n8_tb(kv, da + c * 512 + kk * 2, db + c * 64 + kk * 16, 1);
        WG_COMMIT();
      }
      WG_WAIT(0);
      fence_regs(kv);
      const uint32_t p0 = pack_bf16(kv[0] * ratio0, kv[1] * ratio0), p1 = pack_bf16(kv[2] * ratio1, kv[3] * ratio1);
      asm volatile("st.shared.u32 [%0], %1;" ::"r"(sb + OFF_KVO + (wq * 16 + g) * 16 + t4 * 4), "r"(p0) : "memory");
      asm volatile("st.shared.u32 [%0], %1;" ::"r"(sb + OFF_KVO + (wq * 16 + g + 8) * 16 + t4 * 4), "r"(p1) : "memory");
      fence_async_smem();
      bar_sync(1, 128);
      const uint32_t epoch = get_epoch();
      if (wq == 0) warp_bulk_store(g_s.kv[epoch & 1] + (rb >> 1) * 512 + j * 128 + (rb & 1) * 64, sb + OFF_KVO, 1024);
      warp_arrive(bars + 8 * B_KVMMA);
      float n0 = bf_lo(p0) * bf_lo(p0) + bf_hi(p0) * bf_hi(p0), n1 = bf_lo(p1) * bf_lo(p1) + bf_hi(p1) * bf_hi(p1);
      n0 += __shfl_xor_sync(0xffffffffu, n0, 1); n1 += __shfl_xor_sync(0xffffffffu, n1, 1);
      n0 += __shfl_xor_sync(0xffffffffu, n0, 2); n1 += __shfl_xor_sync(0xffffffffu, n1, 2);
      asm("max.NaN.f32 %0, %1, %2;" : "=f"(n0) : "f"(n0), "f"(n1));
#pragma unroll
      for (int o = 4; o < 32; o <<= 1) {
        const float t = __shfl_xor_sync(0xffffffffu, n0, o);
        asm("max.NaN.f32 %0, %1, %2;" : "=f"(n0) : "f"(n0), "f"(t));
      }
      if (lane == 0) asm volatile("st.shared.f32 [%0], %1;" ::"r"(sb + OFF_MISC + 16 + wq * 4), "f"(n0) : "memory");
      bar_sync(1, 128);
      if (wq == 0) {
        float m0, m1, m2, m3;
        asm volatile("ld.shared.v4.f32 {%0,%1,%2,%3}, [%4];" : "=f"(m0), "=f"(m1), "=f"(m2), "=f"(m3) : "r"(sb + OFF_MISC + 16) : "memory");
        asm("max.NaN.f32 %0, %1, %2;" : "=f"(m0) : "f"(m0), "f"(m1));
        asm("max.NaN.f32 %0, %1, %2;" : "=f"(m2) : "f"(m2), "f"(m3));
        asm("max.NaN.f32 %0, %1, %2;" : "=f"(m0) : "f"(m0), "f"(m2));
        asm volatile("{.reg .pred p; elect.sync _|p, 0xffffffff; cp.async.bulk.wait_group 0; @p st.relaxed.gpu.global.v2.u32 [%0], {%1,%2};}"
                     ::"l"(g_kvflag + blockIdx.x * 4), "r"(epoch), "r"(__float_as_uint(m0)) : "memory");
        warp_publish(g_s.kvflag2 + blockIdx.x * 8, epoch);
      }
    }
    float acc[64];
#pragma unroll
    for (int i = 0; i < 64; i++) acc[i] = 0.f;
    const uint32_t st_row = wq * 16 + (lane & 7) + ((lane >> 3) & 1) * 8;
    const uint64_t dxa = desc_a(sb + OFF_XA), dact = desc_a(sb + OFF_ACT), dbr = desc_b(sb + OFF_BR);
#define WAIT_B(slot, par) mbar_wait(bars + 8 * B_BFULL + 8 * (slot), par)
#define REL_B(i) warp_arrive(bars + 8 * B_BEMPTY + 8 * ((i) & 3), 2)
    mbar_wait(bars + 8 * B_QDONE, 0);
#pragma unroll 1
    for (int t = 0; t < (HELP ? 3 : 4); t++) {
      fence_regs(acc);
      if (HELP || t < 3) {
        WAIT_B(0, 1);
        GEMM_CHUNK(G1DEPTH, wgmma_ss_n128_tb, acc, dxa, dbr, true, );
#pragma unroll
        for (uint32_t c = 1; c < 8; c++) {
          WAIT_B(c & 3, (c >> 2) ^ 1);
          GEMM_CHUNK(G1DEPTH, wgmma_ss_n128_tb, acc, dxa + c * 512, dbr + (c & 3) * 1024, false, REL_B(c - 1));
        }
      } else {
        float (&acc32)[32] = *reinterpret_cast<float (*)[32]>(&acc[0]);
#pragma unroll
        for (int i = 0; i < 32; i++) acc32[i] = 0.f;
        fence_regs(acc32);
#pragma unroll
        for (uint32_t c = 0; c < 4; c++) {
          WAIT_B(c, 1);
          GEMM_CHUNK(G1DEPTH, wgmma_ss_n64_tb, acc32, dxa + c * 1024, dbr + c * 1024, false, if (c > 0) REL_B(c - 1));
          GEMM_CHUNK(G1DEPTH, wgmma_ss_n64_tb, acc32, dxa + c * 1024 + 512, dbr + c * 1024 + 512, false, );
        }
      }
      WG_WAIT(0);
      fence_regs(acc);
      REL_B(3);
      const uint32_t b1a = sb + OFF_B1 + t * 512 + t4 * 8;
      const uint32_t sta = sb + OFF_ACT + t * 16384 + st_row * 128, stx = ((lane >> 4) ^ (st_row & 7)) << 4;
      mish_store<8>(acc, ratio0, ratio1, b1a, sta, stx);
      if (HELP || t < 3) mish_store<8>(*reinterpret_cast<float (*)[64]>(&acc[32]), ratio0, ratio1, b1a + 256, sta + 8192, stx);
      fence_async_smem();
      __syncwarp();
      warp_arrive(bars + 8 * B_ACTT + 8 * t);
    }
    {
      const uint32_t* xp = reinterpret_cast<const uint32_t*>(prm.x + (size_t)(rb * 64 + wq * 16 + g) * D_ + 128 * j) + t4;
#pragma unroll
      for (int c = 0; c < 16; c++) {
        const uint32_t a = __ldg(xp + c * 4), b = __ldg(xp + 8 * (D_ / 2) + c * 4);
        acc[4 * c] = bf_lo(a); acc[4 * c + 1] = bf_hi(a); acc[4 * c + 2] = bf_lo(b); acc[4 * c + 3] = bf_hi(b);
      }
    }
    bar_sync(1, 128);
    fence_regs(acc);
#pragma unroll 4
    for (uint32_t u = 0; u < 28; u++) {
      WAIT_B(u & 3, ((u >> 2) & 1) ^ PH);
      GEMM_CHUNK(G2DEPTH, wgmma_ss_n128_tb, acc, u < NOWN ? dact + u * 512 : dxa + (u & 3) * 512, dbr + (u & 3) * 1024, false,
                 if (u > 0) REL_B(u - 1); if (u == NOWN) warp_arrive(bars + 8 * B_ACTOWN));
    }
    WG_WAIT(0);
    REL_B(3);
    __nv_bfloat16* outp = prm.out + (size_t)(rb * 64 + wq * 16 + (lane >> 4)) * D_ + 128 * j + (lane & 15) * 8;
    uint32_t sta = sb + OFF_XA + 6 * 8192 + wq * 4096 + (st_row & 15) * 256 + (((lane >> 4) ^ (st_row & 7)) << 4);
    uint32_t lda = sb + OFF_XA + 6 * 8192 + wq * 4096 + (lane >> 4) * 256 + (((lane & 15) ^ (lane >> 4)) << 4);
    asm volatile("" : "+l"(outp), "+r"(sta), "+r"(lda));
#pragma unroll 1
    for (uint32_t u = 0; u < 8; u++) {
      const uint32_t bs = u < 6 ? u : u - 6, rem = u < 4 ? u - 1 : u - 2;
      mbar_wait(bars + 8 * B_BFULL + 8 * bs, u < 4 ? 1 ^ PH : u < 6 ? 1 : PH);
      mbar_wait((u & 3) ? bars + 8 * B_OFULL + 8 * rem : bars + 8 * B_OOWN + 2 * u, 0);
      const uint64_t da = (u & 3) ? dact + rem * 512 : dxa + 2048 + u * 128, db = (bs < 4 ? dbr : dbr - 8192) + bs * 1024;
      WG_FENCE();
#pragma unroll
      for (int kk = 0; kk < 4; kk++) wgmma_ss_n128_tb(acc, da + kk * 2, db + kk * 128, 1);
      WG_COMMIT();
      if (u < 2) { WG_WAIT(0); REL_B(u); }
    }
    mbar_wait(bars + 8 * B_OCHK, 0);
    const bool repair = any_of4(sb + OFF_MISC + 64);
    WG_WAIT(0);
    if (__builtin_expect(repair, 0)) {
      warp_arrive(bars + 8 * B_OMMA);
      bar_sync(1, 128);
      if (wq == 0) warp_tma(sb + OFF_XA, &map_wo, 128 * ((j + 1) & 3), 2 * j, bars + 8 * B_QFULL);
      mbar_wait(bars + 8 * B_QFULL, 0);
      mbar_wait(bars + 8 * B_OFIX, 0);
      fence_regs(acc);
#pragma unroll 1
      for (uint32_t l = 0; l < 6; l++) {
        const uint64_t db = l == 0 ? dbr - 4096 : l == 3 ? dbr - 3072 : dbr + (l < 3 ? l + 1 : l - 4) * 1024;
        WG_FENCE();
#pragma unroll
        for (int kk = 0; kk < 4; kk++) wgmma_ss_n128_tb(acc, dact + l * 512 + kk * 2, db + kk * 128, 1);
        WG_COMMIT(); WG_WAIT(0);
      }
    }
    fence_regs(acc);
    {
#pragma unroll
      for (int c = 0; c < 16; c += 2)
        stsm_x4(sta ^ (c << 4), pack_bf16(acc[4 * c], acc[4 * c + 1]), pack_bf16(acc[4 * c + 2], acc[4 * c + 3]),
                pack_bf16(acc[4 * c + 4], acc[4 * c + 5]), pack_bf16(acc[4 * c + 6], acc[4 * c + 7]));
      __syncwarp();
#pragma unroll
      for (int i = 0; i < 8; i++) {
        uint4 v;
        asm volatile("ld.shared.v4.u32 {%0,%1,%2,%3}, [%4];" : "=r"(v.x), "=r"(v.y), "=r"(v.z), "=r"(v.w)
                     : "r"((lda ^ ((2 * i & 7) << 4)) + i * 512) : "memory");
        asm volatile("st.global.v4.u32 [%0], {%1,%2,%3,%4};" ::"l"(outp + 2 * i * D_), "r"(v.x), "r"(v.y), "r"(v.z), "r"(v.w) : "memory");
      }
    }
  }
}

typedef CUresult (*EncodeFn)(CUtensorMap*, CUtensorMapDataType, cuuint32_t, void*, const cuuint64_t*, const cuuint64_t*,
                             const cuuint32_t*, const cuuint32_t*, CUtensorMapInterleave, CUtensorMapSwizzle,
                             CUtensorMapL2promotion, CUtensorMapFloatOOBfill);

void make_map(EncodeFn fn, CUtensorMap* m, const void* p, uint64_t rows, uint64_t cols, uint32_t box_rows, uint32_t box_groups) {
  const cuuint64_t dims[3] = {64, rows, cols / 64};
  const cuuint64_t strides[2] = {cols * 2, 128};
  const cuuint32_t box[3] = {64, box_rows, box_groups}, es[3] = {1, 1, 1};
  fn(m, CU_TENSOR_MAP_DATA_TYPE_BFLOAT16, 3, const_cast<void*>(p), dims, strides, box, es, CU_TENSOR_MAP_INTERLEAVE_NONE,
     CU_TENSOR_MAP_SWIZZLE_128B, CU_TENSOR_MAP_L2_PROMOTION_L2_128B, CU_TENSOR_MAP_FLOAT_OOB_FILL_NONE);
}

}

extern "C" void kernel_launch(void* const* d_in, const int* in_sizes, int n_in, void* d_out, int out_size) {
  (void)in_sizes; (void)n_in; (void)out_size;
  void* fnp = nullptr;
  cudaDriverEntryPointQueryResult qr;
  cudaGetDriverEntryPoint("cuTensorMapEncodeTiled", &fnp, cudaEnableDefault, &qr);
  EncodeFn fn = reinterpret_cast<EncodeFn>(fnp);
  CUtensorMap mq, m1, m1t, m2, mo;
  make_map(fn, &mq, d_in[1], D_, D_, 64, 2);
  make_map(fn, &m1, d_in[6], D_, F_, 64, 2);
  make_map(fn, &m1t, d_in[6], D_, F_, 128, 1);
  make_map(fn, &m2, d_in[8], F_, D_, 64, 2);
  make_map(fn, &mo, d_in[4], D_, D_, 64, 2);
  Params p;
  p.x = (const __nv_bfloat16*)d_in[0]; p.wq = (const __nv_bfloat16*)d_in[1]; p.wk = (const __nv_bfloat16*)d_in[2]; p.wv = (const __nv_bfloat16*)d_in[3];
  p.b1 = (const __nv_bfloat16*)d_in[7]; p.w1 = (const __nv_bfloat16*)d_in[6]; p.w2 = (const __nv_bfloat16*)d_in[8];
  p.wo = (const __nv_bfloat16*)d_in[4]; p.out = (__nv_bfloat16*)d_out;
  int dev = 0, sms = 0;
  cudaGetDevice(&dev);
  cudaDeviceGetAttribute(&sms, cudaDevAttrMultiProcessorCount, dev);
  if (USE_HELP && sms >= NCTA + 4) {
    cudaFuncSetAttribute(fused_kernel<true>, cudaFuncAttributeMaxDynamicSharedMemorySize, SMEM_BYTES);
    fused_kernel<true><<<NCTA + 4, 512, SMEM_BYTES>>>(p, mq, m1, m1t, m2, mo);
  } else {
    cudaFuncSetAttribute(fused_kernel<false>, cudaFuncAttributeMaxDynamicSharedMemorySize, SMEM_BYTES);
    fused_kernel<false><<<NCTA, 512, SMEM_BYTES>>>(p, mq, m1, m1t, m2, mo);
  }
}
```
